```python
import torch

def _softmax(x, axis=-1):
    return torch.softmax(x, dim=axis)

def _gelu(x):
    return torch.nn.functional.gelu(x, approximate='tanh')

def _silu(x):
    return torch.nn.functional.silu(x)

def _sigmoid(x):
    return torch.sigmoid(x)

def _layernorm(x, axis=-1, eps=1e-05):
    m = x.mean(dim=axis, keepdim=True)
    v = x.var(dim=axis, keepdim=True, unbiased=False)
    return (x - m) / torch.sqrt(v + eps)

def _scatter_add(tgt, idx, src, axis=0):
    return tgt.clone().index_add_(axis, idx, src)

def _segment_sum(src, seg, n):
    out = torch.zeros((n,) + src.shape[1:], dtype=src.dtype)
    return out.index_add_(0, seg, src)

def _pad(x, pw):
    flat = tuple((v for pair in reversed(pw) for v in pair))
    return torch.nn.functional.pad(x, flat)
kernel_name = 'sequential_preLN__mha_block__mixer_gmlp__prompt'

def setup_inputs():

    _w = lambda a: (lambda t: t.to(torch.bfloat16) if t.is_floating_point() else t)(torch.as_tensor(a))

    def _A_setup():
        B, S, D, H = (1, 2048, 512, 32)
        return {'x': _w((lambda *s: torch.randn(*s, dtype=torch.bfloat16) * 0.05)(B, S, D)), 'wqkv': _w((lambda *s: torch.randn(*s, dtype=torch.bfloat16) * 0.05)(D, 3 * D)), 'wo': _w((lambda *s: torch.randn(*s, dtype=torch.bfloat16) * 0.05)(D, D))}
    _A_in = _A_setup()

    def _B_setup():
        B, S, D, F = (1, 2048, 512, 1792)
        Fh = F // 2
        return {'x': _w((lambda *s: torch.randn(*s, dtype=torch.bfloat16) * 0.05)(B, S, D)), 'w_in': _w((lambda *s: torch.randn(*s, dtype=torch.bfloat16) * 0.4)(D, 2 * Fh)), 'w_sp': _w(0.01 * (lambda *s: torch.randn(*s, dtype=torch.bfloat16) * 0.4)(S, S)), 'b_sp': _w(1.0 + 0.01 * (lambda *s: torch.randn(*s, dtype=torch.bfloat16) * 0.05)(S)), 'w_out': _w((lambda *s: torch.randn(*s, dtype=torch.bfloat16) * 0.05)(Fh, D))}
    _B_in = _B_setup()
    return {'A_x': _A_in['x'], 'A_wqkv': _A_in['wqkv'], 'A_wo': _A_in['wo'], 'B_x': _B_in['x'], 'B_w_in': _B_in['w_in'], 'B_w_sp': _B_in['w_sp'], 'B_b_sp': _B_in['b_sp'], 'B_w_out': _B_in['w_out']}

def reference(A_x, A_wqkv, A_wo, B_x, B_w_in, B_w_sp, B_b_sp, B_w_out):

    def _A_ref(x, wqkv, wo):
        B, S, D = x.shape
        H = 32
        Dh = D // H
        qkv = (lambda x, *d: x.permute(*d))((x @ wqkv).reshape(B, S, 3, H, Dh), 2, 0, 3, 1, 4)
        q, k, v = (qkv[0], qkv[1], qkv[2])
        scores = torch.einsum('bhqd,bhkd->bhqk', q, k) * Dh ** (-0.5)
        p = _softmax(scores, axis=-1)
        o = torch.einsum('bhqk,bhkd->bhqd', p, v)
        return (lambda x, *d: x.permute(*d))(o, 0, 2, 1, 3).reshape(B, S, D) @ wo

    def _B_ref(x, w_in, w_sp, b_sp, w_out):
        B, S, D = x.shape
        F = w_in.shape[-1]
        Fh = F // 2
        z = _gelu(torch.einsum('bsd,df->bsf', x, w_in))
        z1 = z[..., :Fh].clone()
        z2 = _layernorm(z[..., Fh:], axis=-1)
        g = torch.einsum('ts,bsf->btf', w_sp, z2) + b_sp[None, :, None]
        return torch.einsum('bsf,fd->bsd', z1 * g, w_out)
    x = A_x
    h = x + _A_ref(_layernorm(x, axis=-1), A_wqkv, A_wo)
    h2 = h + _B_ref(_layernorm(h, axis=-1), B_w_in, B_w_sp, B_b_sp, B_w_out)
    return h2
```

```cpp
#include <cuda_runtime.h>
#include <cuda_bf16.h>
#include <cuda.h>
#include <stdint.h>

namespace {

constexpr int SEQ = 2048, DM = 512, NH = 32, FF = 1792, FH = 896;
constexpr float LN_EPS = 1e-5f;

__device__ __align__(1024) uint32_t g_q[NH * SEQ * 8];
__device__ __align__(1024) uint32_t g_k[NH * SEQ * 8];
__device__ __align__(1024) uint32_t g_v[NH * SEQ * 8];
__device__ __align__(16) float2 g_kv[NH * 128];
__device__ __align__(1024) uint32_t g_o[SEQ * DM / 2];
__device__ __align__(1024) uint32_t g_h[SEQ * DM / 2];
__device__ __align__(16) float2 g_hstat[SEQ * 8];
__device__ __align__(16) float2 g_zstat[SEQ * 8];
__device__ __align__(16) float g_csin[FF];
__device__ __align__(1024) uint32_t g_z2[SEQ * FH / 2];
__device__ __align__(1024) uint4 g_z1[SEQ * FH / 8];
__device__ __align__(1024) uint32_t g_u[SEQ * FH / 2];

__device__ __forceinline__ uint32_t smem_u32(const void* p) { return (uint32_t)__cvta_generic_to_shared(p); }
__device__ __forceinline__ void mbar_init(uint32_t bar, uint32_t cnt) {
    asm volatile("mbarrier.init.shared::cta.b64 [%0], %1;" ::"r"(bar), "r"(cnt) : "memory");
}
__device__ __forceinline__ void mbar_expect_tx(uint32_t bar, uint32_t bytes) {
    asm volatile("mbarrier.arrive.expect_tx.shared::cta.b64 _, [%0], %1;" ::"r"(bar), "r"(bytes) : "memory");
}
__device__ __forceinline__ void mbar_arrive(uint32_t bar) {
    asm volatile("mbarrier.arrive.shared::cta.b64 _, [%0];" ::"r"(bar) : "memory");
}
__device__ __forceinline__ uint32_t mbar_try(uint32_t bar, uint32_t parity) {
    uint32_t done;
    asm volatile("{\n.reg .pred p;\nmbarrier.try_wait.parity.shared::cta.b64 p, [%1], %2;\nselp.u32 %0, 1, 0, p;\n}\n"
                 : "=r"(done) : "r"(bar), "r"(parity) : "memory");
    return done;
}
__device__ __noinline__ void mbar_wait_slow(uint32_t bar, uint32_t parity) {
    long long t0 = clock64();
    while (!mbar_try(bar, parity)) {
        if (clock64() - t0 > 2000000000LL) { asm volatile("trap;"); }
    }
}
__device__ __forceinline__ void mbar_wait(uint32_t bar, uint32_t parity) {
    if (!mbar_try(bar, parity)) {
        if (!mbar_try(bar, parity)) mbar_wait_slow(bar, parity);
    }
}
__device__ __forceinline__ void fence_mbar_init() { asm volatile("fence.mbarrier_init.release.cluster;" ::: "memory"); }
__device__ __forceinline__ void fence_proxy_async() { asm volatile("fence.proxy.async.shared::cta;" ::: "memory"); }
__device__ __forceinline__ void tma_load_2d(uint32_t dst, const CUtensorMap* tm, int c0, int c1, uint32_t bar) {
    asm volatile("cp.async.bulk.tensor.2d.shared::cluster.global.mbarrier::complete_tx::bytes [%0], [%1, {%3, %4}], [%2];"
                 ::"r"(dst), "l"(tm), "r"(bar), "r"(c0), "r"(c1) : "memory");
}
__device__ __forceinline__ void tma_store_2d(const CUtensorMap* tm, uint32_t src, int c0, int c1) {
    asm volatile("cp.async.bulk.tensor.2d.global.shared::cta.bulk_group [%0, {%2, %3}], [%1];"
                 ::"l"(tm), "r"(src), "r"(c0), "r"(c1) : "memory");
}
__device__ __forceinline__ void bulk_load(uint32_t dst, const void* src, uint32_t bytes, uint32_t bar) {
    asm volatile("cp.async.bulk.shared::cluster.global.mbarrier::complete_tx::bytes [%0], [%1], %2, [%3];"
                 ::"r"(dst), "l"(src), "r"(bytes), "r"(bar) : "memory");
}
__device__ __forceinline__ void l2_prefetch(const void* src, uint32_t bytes) {
    asm volatile("cp.async.bulk.prefetch.L2.global [%0], %1;" ::"l"(src), "r"(bytes) : "memory");
}
__device__ __forceinline__ void tm_prefetch(const CUtensorMap* tm) {
    asm volatile("prefetch.tensormap [%0];" ::"l"(tm) : "memory");
}
__device__ __forceinline__ void pdl_wait() { asm volatile("griddepcontrol.wait;" ::: "memory"); }
__device__ __forceinline__ void pdl_launch() { asm volatile("griddepcontrol.launch_dependents;" ::: "memory"); }
__device__ __forceinline__ void wg_fence() { asm volatile("wgmma.fence.sync.aligned;" ::: "memory"); }
__device__ __forceinline__ void wg_commit() { asm volatile("wgmma.commit_group.sync.aligned;" ::: "memory"); }
template <int N> __device__ __forceinline__ void wg_wait() { asm volatile("wgmma.wait_group.sync.aligned %0;" ::"n"(N) : "memory"); }
template <int N> __device__ __forceinline__ void reg_fence(float (&d)[N]) {
#pragma unroll
    for (int i = 0; i < N; i++) asm volatile("" : "+f"(d[i])::"memory");
}
template <int N> __device__ __forceinline__ void reg_fence(uint32_t (&d)[N]) {
#pragma unroll
    for (int i = 0; i < N; i++) asm volatile("" : "+r"(d[i])::"memory");
}
__device__ __forceinline__ void bar_sync(int id, int n) { asm volatile("bar.sync %0, %1;" ::"r"(id), "r"(n) : "memory"); }
__device__ __forceinline__ void bar_arrive(int id, int n) { asm volatile("bar.arrive %0, %1;" ::"r"(id), "r"(n) : "memory"); }

__device__ __forceinline__ uint64_t make_desc(uint32_t saddr, uint32_t lbo, uint32_t sbo, uint32_t swz) {
    return (uint64_t)((saddr & 0x3FFFF) >> 4) | ((uint64_t)((lbo & 0x3FFFF) >> 4) << 16) |
           ((uint64_t)((sbo & 0x3FFFF) >> 4) << 32) | ((uint64_t)swz << 62);
}
__device__ __forceinline__ uint32_t pack_bf16(float lo, float hi) {
    uint32_t r;
    asm("cvt.rn.bf16x2.f32 %0, %1, %2;" : "=r"(r) : "f"(hi), "f"(lo));
    return r;
}
__device__ __forceinline__ float bf_lo(uint32_t v) { return __uint_as_float(v << 16); }
__device__ __forceinline__ float bf_hi(uint32_t v) { return __uint_as_float(v & 0xffff0000u); }
__device__ __forceinline__ float ex2(float x) {
    float r;
    asm("ex2.approx.ftz.f32 %0, %1;" : "=f"(r) : "f"(x));
    return r;
}
__device__ __forceinline__ float tanh_fast(float x) {
    float r;
    asm("tanh.approx.f32 %0, %1;" : "=f"(r) : "f"(x));
    return r;
}
__device__ __forceinline__ uint32_t hfma2_bf16(uint32_t a, uint32_t b, uint32_t c) {
    uint32_t r;
    asm("fma.rn.bf16x2 %0, %1, %2, %3;" : "=r"(r) : "r"(a), "r"(b), "r"(c));
    return r;
}
__device__ __forceinline__ uint4 lds128(uint32_t a) {
    uint4 v;
    asm volatile("ld.shared.v4.u32 {%0,%1,%2,%3}, [%4];" : "=r"(v.x), "=r"(v.y), "=r"(v.z), "=r"(v.w) : "r"(a) : "memory");
    return v;
}
__device__ __forceinline__ float gelu_tanh(float x) {
    float u = x * fmaf(x * x, 0.044715f * 0.7978845608028654f, 0.7978845608028654f);
    float hx = 0.5f * x;
    return fmaf(hx, tanh_fast(u), hx);
}

__device__ __forceinline__ void wgmma_ss_n192_t(float (&d)[96], uint64_t da, uint64_t db, int acc) {
    asm volatile("{\n.reg .pred p;\nsetp.ne.b32 p, %98, 0;\n"
        "wgmma.mma_async.sync.aligned.m64n192k16.f32.bf16.bf16 {%0,%1,%2,%3,%4,%5,%6,%7,%8,%9,%10,%11,%12,%13,%14,%15,%16,%17,%18,%19,%20,%21,%22,%23,%24,%25,%26,%27,%28,%29,%30,%31,%32,%33,%34,%35,%36,%37,%38,%39,%40,%41,%42,%43,%44,%45,%46,%47,%48,%49,%50,%51,%52,%53,%54,%55,%56,%57,%58,%59,%60,%61,%62,%63,%64,%65,%66,%67,%68,%69,%70,%71,%72,%73,%74,%75,%76,%77,%78,%79,%80,%81,%82,%83,%84,%85,%86,%87,%88,%89,%90,%91,%92,%93,%94,%95}, %96, %97, p, 1, 1, 0, 1;\n}\n"
        : "+f"(d[0]), "+f"(d[1]), "+f"(d[2]), "+f"(d[3]), "+f"(d[4]), "+f"(d[5]), "+f"(d[6]), "+f"(d[7]), "+f"(d[8]), "+f"(d[9]), "+f"(d[10]), "+f"(d[11]), "+f"(d[12]), "+f"(d[13]), "+f"(d[14]), "+f"(d[15]), "+f"(d[16]), "+f"(d[17]), "+f"(d[18]), "+f"(d[19]), "+f"(d[20]), "+f"(d[21]), "+f"(d[22]), "+f"(d[23]), "+f"(d[24]), "+f"(d[25]), "+f"(d[26]), "+f"(d[27]), "+f"(d[28]), "+f"(d[29]), "+f"(d[30]), "+f"(d[31]), "+f"(d[32]), "+f"(d[33]), "+f"(d[34]), "+f"(d[35]), "+f"(d[36]), "+f"(d[37]), "+f"(d[38]), "+f"(d[39]), "+f"(d[40]), "+f"(d[41]), "+f"(d[42]), "+f"(d[43]), "+f"(d[44]), "+f"(d[45]), "+f"(d[46]), "+f"(d[47]), "+f"(d[48]), "+f"(d[49]), "+f"(d[50]), "+f"(d[51]), "+f"(d[52]), "+f"(d[53]), "+f"(d[54]), "+f"(d[55]), "+f"(d[56]), "+f"(d[57]), "+f"(d[58]), "+f"(d[59]), "+f"(d[60]), "+f"(d[61]), "+f"(d[62]), "+f"(d[63]), "+f"(d[64]), "+f"(d[65]), "+f"(d[66]), "+f"(d[67]), "+f"(d[68]), "+f"(d[69]), "+f"(d[70]), "+f"(d[71]), "+f"(d[72]), "+f"(d[73]), "+f"(d[74]), "+f"(d[75]), "+f"(d[76]), "+f"(d[77]), "+f"(d[78]), "+f"(d[79]), "+f"(d[80]), "+f"(d[81]), "+f"(d[82]), "+f"(d[83]), "+f"(d[84]), "+f"(d[85]), "+f"(d[86]), "+f"(d[87]), "+f"(d[88]), "+f"(d[89]), "+f"(d[90]), "+f"(d[91]), "+f"(d[92]), "+f"(d[93]), "+f"(d[94]), "+f"(d[95])
        : "l"(da), "l"(db), "r"(acc));
}

__device__ __forceinline__ void wgmma_ss_n112_t(float (&d)[56], uint64_t da, uint64_t db, int acc) {
    asm volatile("{\n.reg .pred p;\nsetp.ne.b32 p, %58, 0;\n"
        "wgmma.mma_async.sync.aligned.m64n112k16.f32.bf16.bf16 {%0,%1,%2,%3,%4,%5,%6,%7,%8,%9,%10,%11,%12,%13,%14,%15,%16,%17,%18,%19,%20,%21,%22,%23,%24,%25,%26,%27,%28,%29,%30,%31,%32,%33,%34,%35,%36,%37,%38,%39,%40,%41,%42,%43,%44,%45,%46,%47,%48,%49,%50,%51,%52,%53,%54,%55}, %56, %57, p, 1, 1, 0, 1;\n}\n"
        : "+f"(d[0]), "+f"(d[1]), "+f"(d[2]), "+f"(d[3]), "+f"(d[4]), "+f"(d[5]), "+f"(d[6]), "+f"(d[7]), "+f"(d[8]), "+f"(d[9]), "+f"(d[10]), "+f"(d[11]), "+f"(d[12]), "+f"(d[13]), "+f"(d[14]), "+f"(d[15]), "+f"(d[16]), "+f"(d[17]), "+f"(d[18]), "+f"(d[19]), "+f"(d[20]), "+f"(d[21]), "+f"(d[22]), "+f"(d[23]), "+f"(d[24]), "+f"(d[25]), "+f"(d[26]), "+f"(d[27]), "+f"(d[28]), "+f"(d[29]), "+f"(d[30]), "+f"(d[31]), "+f"(d[32]), "+f"(d[33]), "+f"(d[34]), "+f"(d[35]), "+f"(d[36]), "+f"(d[37]), "+f"(d[38]), "+f"(d[39]), "+f"(d[40]), "+f"(d[41]), "+f"(d[42]), "+f"(d[43]), "+f"(d[44]), "+f"(d[45]), "+f"(d[46]), "+f"(d[47]), "+f"(d[48]), "+f"(d[49]), "+f"(d[50]), "+f"(d[51]), "+f"(d[52]), "+f"(d[53]), "+f"(d[54]), "+f"(d[55])
        : "l"(da), "l"(db), "r"(acc));
}

__device__ __forceinline__ void wgmma_ss_n64_t(float (&d)[32], uint64_t da, uint64_t db, int acc) {
    asm volatile("{\n.reg .pred p;\nsetp.ne.b32 p, %34, 0;\n"
        "wgmma.mma_async.sync.aligned.m64n64k16.f32.bf16.bf16 {%0,%1,%2,%3,%4,%5,%6,%7,%8,%9,%10,%11,%12,%13,%14,%15,%16,%17,%18,%19,%20,%21,%22,%23,%24,%25,%26,%27,%28,%29,%30,%31}, %32, %33, p, 1, 1, 0, 1;\n}\n"
        : "+f"(d[0]), "+f"(d[1]), "+f"(d[2]), "+f"(d[3]), "+f"(d[4]), "+f"(d[5]), "+f"(d[6]), "+f"(d[7]), "+f"(d[8]), "+f"(d[9]), "+f"(d[10]), "+f"(d[11]), "+f"(d[12]), "+f"(d[13]), "+f"(d[14]), "+f"(d[15]), "+f"(d[16]), "+f"(d[17]), "+f"(d[18]), "+f"(d[19]), "+f"(d[20]), "+f"(d[21]), "+f"(d[22]), "+f"(d[23]), "+f"(d[24]), "+f"(d[25]), "+f"(d[26]), "+f"(d[27]), "+f"(d[28]), "+f"(d[29]), "+f"(d[30]), "+f"(d[31])
        : "l"(da), "l"(db), "r"(acc));
}

__device__ __forceinline__ void wgmma_rs_n64_z(float (&d)[32], uint32_t a0, uint32_t a1, uint32_t a2, uint32_t a3, uint64_t db) {
    asm volatile("wgmma.mma_async.sync.aligned.m64n64k16.f32.bf16.bf16 {%0,%1,%2,%3,%4,%5,%6,%7,%8,%9,%10,%11,%12,%13,%14,%15,%16,%17,%18,%19,%20,%21,%22,%23,%24,%25,%26,%27,%28,%29,%30,%31}, {%32,%33,%34,%35}, %36, 0, 1, 1, 0;\n"
        : "=f"(d[0]), "=f"(d[1]), "=f"(d[2]), "=f"(d[3]), "=f"(d[4]), "=f"(d[5]), "=f"(d[6]), "=f"(d[7]), "=f"(d[8]), "=f"(d[9]), "=f"(d[10]), "=f"(d[11]), "=f"(d[12]), "=f"(d[13]), "=f"(d[14]), "=f"(d[15]), "=f"(d[16]), "=f"(d[17]), "=f"(d[18]), "=f"(d[19]), "=f"(d[20]), "=f"(d[21]), "=f"(d[22]), "=f"(d[23]), "=f"(d[24]), "=f"(d[25]), "=f"(d[26]), "=f"(d[27]), "=f"(d[28]), "=f"(d[29]), "=f"(d[30]), "=f"(d[31])
        : "r"(a0), "r"(a1), "r"(a2), "r"(a3), "l"(db));
}

__device__ __forceinline__ void wgmma_rs_n24_t(float (&d)[12], uint32_t a0, uint32_t a1, uint32_t a2, uint32_t a3, uint64_t db) {
    asm volatile("wgmma.mma_async.sync.aligned.m64n24k16.f32.bf16.bf16 {%0,%1,%2,%3,%4,%5,%6,%7,%8,%9,%10,%11}, {%12,%13,%14,%15}, %16, 1, 1, 1, 1;\n"
        : "+f"(d[0]), "+f"(d[1]), "+f"(d[2]), "+f"(d[3]), "+f"(d[4]), "+f"(d[5]), "+f"(d[6]), "+f"(d[7]), "+f"(d[8]), "+f"(d[9]), "+f"(d[10]), "+f"(d[11])
        : "r"(a0), "r"(a1), "r"(a2), "r"(a3), "l"(db));
}


constexpr int P1_STAGES = 5;
constexpr int P1_STAGE_BYTES = 16384 + 24576;
constexpr int P1_AUX = P1_STAGES * P1_STAGE_BYTES;
constexpr int P1_SMEM = P1_AUX + 128 + 128 * 8 + 192 * 4;

__global__ void __launch_bounds__(416, 1)
k_qkv(const __grid_constant__ CUtensorMap tm_x, const __grid_constant__ CUtensorMap tm_w) {
    extern __shared__ __align__(1024) uint8_t smem[];
    const uint32_t sb = smem_u32(smem);
    const uint32_t bar_full = sb + P1_AUX, bar_empty = bar_full + 8 * P1_STAGES;
    float2* s_row = reinterpret_cast<float2*>(smem + P1_AUX + 128);
    float* s_cs = reinterpret_cast<float*>(smem + P1_AUX + 128 + 1024);
    const int tid = threadIdx.x, warp = tid >> 5, lane = tid & 31;
    const int rb = blockIdx.x >> 3, c = blockIdx.x & 7;
    if (tid == 0) {
        if (sb & 1023) asm volatile("trap;");
        for (int s = 0; s < P1_STAGES; s++) { mbar_init(bar_full + 8 * s, 1); mbar_init(bar_empty + 8 * s, 12); }
        fence_mbar_init();
    }
    __syncthreads();
    pdl_launch();
    if (warp == 12) {
        if (lane == 0) {
            for (int kb = 0; kb < 8; kb++) {
                int s = kb % P1_STAGES;
                if (kb >= P1_STAGES) mbar_wait(bar_empty + 8 * s, 0);
                uint32_t st = sb + s * P1_STAGE_BYTES, fb = bar_full + 8 * s;
                mbar_expect_tx(fb, P1_STAGE_BYTES);
                tma_load_2d(st, &tm_x, kb * 64, rb * 128, fb);
                tma_load_2d(st + 16384, &tm_w, c * 64, kb * 64, fb);
                tma_load_2d(st + 16384 + 8192, &tm_w, 512 + c * 64, kb * 64, fb);
                tma_load_2d(st + 16384 + 16384, &tm_w, 1024 + c * 64, kb * 64, fb);
            }
        }
    } else if (warp >= 8) {
        const int t = tid - 256;
        float rs = 0.f, rq = 0.f;
        float cs[8];
#pragma unroll
        for (int i = 0; i < 8; i++) cs[i] = 0.f;
        const int ch = lane & 7, rsub = lane >> 3, box = warp - 8;
        for (int kb = 0; kb < 8; kb++) {
            int s = kb % P1_STAGES;
            mbar_wait(bar_full + 8 * s, (kb / P1_STAGES) & 1);
            uint32_t st = sb + s * P1_STAGE_BYTES;
            uint32_t ra = st + t * 128;
#pragma unroll
            for (int i = 0; i < 8; i++) {
                uint4 v = lds128(ra + ((i ^ (t & 7)) << 4));
                uint32_t w[4] = {v.x, v.y, v.z, v.w};
#pragma unroll
                for (int e = 0; e < 4; e++) {
                    float a = bf_lo(w[e]), b = bf_hi(w[e]);
                    rs += a; rq = fmaf(a, a, rq);
                    rs += b; rq = fmaf(b, b, rq);
                }
            }
            if (box < 3) {
                uint32_t ba = st + 16384 + box * 8192;
#pragma unroll
                for (int i = 0; i < 16; i++) {
                    int r = rsub + 4 * i;
                    uint4 v = lds128(ba + r * 128 + ((ch ^ (r & 7)) << 4));
                    cs[0] += bf_lo(v.x); cs[1] += bf_hi(v.x);
                    cs[2] += bf_lo(v.y); cs[3] += bf_hi(v.y);
                    cs[4] += bf_lo(v.z); cs[5] += bf_hi(v.z);
                    cs[6] += bf_lo(v.w); cs[7] += bf_hi(v.w);
                }
            }
            __syncwarp();
            if (lane == 0) mbar_arrive(bar_empty + 8 * s);
        }
        float mean = rs * (1.f / DM);
        float var = fmaxf(rq * (1.f / DM) - mean * mean, 0.f);
        s_row[t] = make_float2(mean, rsqrtf(var + LN_EPS));
        if (box < 3) {
#pragma unroll
            for (int i = 0; i < 8; i++) {
                cs[i] += __shfl_xor_sync(0xffffffffu, cs[i], 8);
                cs[i] += __shfl_xor_sync(0xffffffffu, cs[i], 16);
            }
            if (rsub == 0) {
#pragma unroll
                for (int i = 0; i < 8; i++) s_cs[box * 64 + ch * 8 + i] = cs[i];
            }
        }
        bar_arrive(1, 384);
    } else {
        const int wg = warp >> 2;
        float acc[96];
        for (int kb = 0; kb < 8; kb++) {
            int s = kb % P1_STAGES;
            mbar_wait(bar_full + 8 * s, (kb / P1_STAGES) & 1);
            uint32_t st = sb + s * P1_STAGE_BYTES;
            uint64_t da = make_desc(st + wg * 8192, 16, 1024, 1);
            uint64_t db = make_desc(st + 16384, 8192, 1024, 1);
            wg_fence();
#pragma unroll
            for (int k = 0; k < 4; k++) wgmma_ss_n192_t(acc, da + k * 2, db + k * 128, kb | k);
            wg_commit();
            if (kb > 0) {
                wg_wait<1>();
                if (lane == 0) mbar_arrive(bar_empty + 8 * ((kb - 1) % P1_STAGES));
            }
        }
        wg_wait<0>();
        reg_fence(acc);
        bar_sync(1, 384);
        const int q4 = lane & 3;
        const int r0 = warp * 16 + (lane >> 2);
        const float2 st0 = s_row[r0], st1 = s_row[r0 + 8];
        const int rg = rb * 16 + warp * 2;
        constexpr float QS = 0.25f * 1.4426950408889634f;
        float vmax = 0.f;
        float kn[4];
#pragma unroll
        for (int j = 0; j < 24; j++) {
            const int sec = j >> 3, jj = j & 7, head = 4 * c + (jj >> 1), half = jj & 1;
            float2 csv = *reinterpret_cast<const float2*>(&s_cs[j * 8 + q4 * 2]);
            float sc0 = sec == 0 ? st0.y * QS : st0.y, sc1 = sec == 0 ? st1.y * QS : st1.y;
            float v0 = sc0 * fmaf(-st0.x, csv.x, acc[4 * j + 0]);
            float v1 = sc0 * fmaf(-st0.x, csv.y, acc[4 * j + 1]);
            float v2 = sc1 * fmaf(-st1.x, csv.x, acc[4 * j + 2]);
            float v3 = sc1 * fmaf(-st1.x, csv.y, acc[4 * j + 3]);
            uint32_t p0 = pack_bf16(v0, v1), p1 = pack_bf16(v2, v3);
            if (sec < 2) {
                uint32_t* dst = (sec == 0 ? g_q : g_k) + ((head * 256 + rg) * 2 + half) * 32 + lane;
                dst[0] = p0;
                dst[64] = p1;
            } else {
                uint32_t* dst = g_v + ((head * 2 + half) * 256 + rg) * 32 + lane;
                dst[0] = p0;
                dst[32] = p1;
            }
            if (sec == 1) {
                acc[4 * j + 0] = v0 * v0 + v1 * v1;
                acc[4 * j + 2] = v2 * v2 + v3 * v3;
            }
            if (sec == 2) {
                uint32_t m = max(max(__float_as_uint(fabsf(v0)), __float_as_uint(fabsf(v1))),
                                 max(__float_as_uint(fabsf(v2)), __float_as_uint(fabsf(v3))));
                vmax = __uint_as_float(max(__float_as_uint(vmax), m));
            }
        }
#pragma unroll
        for (int hh = 0; hh < 4; hh++) {
            float a = acc[4 * (8 + 2 * hh) + 0] + acc[4 * (9 + 2 * hh) + 0];
            float b = acc[4 * (8 + 2 * hh) + 2] + acc[4 * (9 + 2 * hh) + 2];
            a += __shfl_xor_sync(0xffffffffu, a, 1); b += __shfl_xor_sync(0xffffffffu, b, 1);
            a += __shfl_xor_sync(0xffffffffu, a, 2); b += __shfl_xor_sync(0xffffffffu, b, 2);
            uint32_t m = max(__float_as_uint(fabsf(a)), __float_as_uint(fabsf(b)));
            m = __reduce_max_sync(0xffffffffu, m);
            kn[hh] = __uint_as_float(m);
        }
        uint32_t vm = __reduce_max_sync(0xffffffffu, __float_as_uint(vmax));
        if (lane < 4) {
            float kk = lane == 0 ? kn[0] : lane == 1 ? kn[1] : lane == 2 ? kn[2] : kn[3];
            g_kv[(4 * c + lane) * 128 + rb * 8 + warp] = make_float2(kk, __uint_as_float(vm));
        }
    }
}

constexpr int P2_K = 0, P2_V = 65536, P2_ONES = 131072, P2_AUX = 163840;
constexpr int P2_SMEM = P2_AUX + 256;
constexpr int P2_NCH = 8;

__device__ __forceinline__ uint32_t exp2_pair_mufu(float x0, float x1) { return pack_bf16(ex2(x0), ex2(x1)); }
__device__ __forceinline__ uint32_t exp2_pair_fma(float x0, float x1) {
    constexpr float MAGIC = 8388608.f + 127.f * 32768.f + 128.f;
    float t0 = fmaf(x0, 32768.f, MAGIC), t1 = fmaf(x1, 32768.f, MAGIC);
    uint32_t u = __byte_perm(__float_as_uint(t0), __float_as_uint(t1), 0x6521);
    uint32_t m = (u & 0x007F007Fu) | 0x3F803F80u;
    uint32_t d = hfma2_bf16(0x3E723E72u, m, 0xBF33BF33u);
    d = hfma2_bf16(d, m, 0x3EEB3EEBu);
    return hfma2_bf16(u, d, u);
}
template <int OFF> __device__ __forceinline__ void exp_half(const float (&s)[32], uint32_t (&p)[16]) {
#pragma unroll
    for (int i = 0; i < 8; i++) {
        const int idx = OFF + i;
        if (i == 1 || i == 4 || i == 6) p[idx] = exp2_pair_mufu(s[2 * idx], s[2 * idx + 1]);
        else p[idx] = exp2_pair_fma(s[2 * idx], s[2 * idx + 1]);
    }
}

__device__ __forceinline__ void attn_step(float (&cur)[32], float (&nxt)[32], uint32_t (&p)[16], float (&o)[12],
                                          const uint32_t (&q)[4], uint64_t dk, uint64_t dv, int j, bool first,
                                          uint32_t bar_kv) {
    wg_wait<1>();
    reg_fence(cur);
    if (j + 1 < 32) {
        if (first && ((j + 1) & 3) == 0) mbar_wait(bar_kv + 8 * ((j + 1) >> 2), 0);
        wg_fence();
        wgmma_rs_n64_z(nxt, q[0], q[1], q[2], q[3], dk + (uint64_t)(j + 1) * 128);
    }
    wg_commit();
    exp_half<0>(cur, p);
    wg_fence();
    wgmma_rs_n24_t(o, p[0], p[1], p[2], p[3], dv + (uint64_t)(j * 4 + 0) * 16);
    wgmma_rs_n24_t(o, p[4], p[5], p[6], p[7], dv + (uint64_t)(j * 4 + 1) * 16);
    wg_commit();
    wg_wait<2>();
    exp_half<8>(cur, p);
    wg_fence();
    wgmma_rs_n24_t(o, p[8], p[9], p[10], p[11], dv + (uint64_t)(j * 4 + 2) * 16);
    wgmma_rs_n24_t(o, p[12], p[13], p[14], p[15], dv + (uint64_t)(j * 4 + 3) * 16);
    wg_commit();
}

__global__ void __launch_bounds__(512, 1)
k_attn(const __nv_bfloat16* __restrict__ w_in, const __nv_bfloat16* __restrict__ wo,
       const __nv_bfloat16* __restrict__ w_sp, const __nv_bfloat16* __restrict__ w_out) {
    extern __shared__ __align__(1024) uint8_t smem[];
    const uint32_t sb = smem_u32(smem);
    const int tid = threadIdx.x, warp = tid >> 5, lane = tid & 31;
    if (blockIdx.x >= 128) {
        pdl_launch();
        pdl_wait();
        const int sp = blockIdx.x - 128;
        if (tid < 64) l2_prefetch(reinterpret_cast<const uint8_t*>(w_sp) + (size_t)(sp * 64 + tid) * 32768, 32768);
        else if (tid < 68) l2_prefetch(reinterpret_cast<const uint8_t*>(wo) + (size_t)(sp * 4 + tid - 64) * 32768, 32768);
        else if (tid < 75) l2_prefetch(reinterpret_cast<const uint8_t*>(w_out) + (size_t)(sp * 7 + tid - 68) * 32768, 32768);
        float* red = reinterpret_cast<float*>(smem);
        if (tid < 448) {
            const int cc = tid % 56, sl = tid / 56;
            const uint4* src = reinterpret_cast<const uint4*>(w_in + (size_t)sl * 64 * FF + sp * 448 + cc * 8);
            float cs[8];
#pragma unroll
            for (int i = 0; i < 8; i++) cs[i] = 0.f;
#pragma unroll 16
            for (int r = 0; r < 64; r++) {
                uint4 v = __ldg(src + (size_t)r * (FF / 8));
                cs[0] += bf_lo(v.x); cs[1] += bf_hi(v.x);
                cs[2] += bf_lo(v.y); cs[3] += bf_hi(v.y);
                cs[4] += bf_lo(v.z); cs[5] += bf_hi(v.z);
                cs[6] += bf_lo(v.w); cs[7] += bf_hi(v.w);
            }
#pragma unroll
            for (int i = 0; i < 8; i++) red[sl * 448 + cc * 8 + i] = cs[i];
        }
        __syncthreads();
        if (tid < 448) {
            float s = 0.f;
#pragma unroll
            for (int i = 0; i < 8; i++) s += red[i * 448 + tid];
            g_csin[sp * 448 + tid] = s;
        }
        return;
    }
    const int head = blockIdx.x >> 2, qq = blockIdx.x & 3;
    const uint32_t bar_kv = sb + P2_AUX;
    uint32_t* s_red = reinterpret_cast<uint32_t*>(smem + P2_AUX + 64);
    if (tid == 0) {
        if (sb & 1023) asm volatile("trap;");
        for (int i = 0; i < P2_NCH; i++) mbar_init(bar_kv + 8 * i, 1);
        fence_mbar_init();
    }
    {
        uint4 ones = make_uint4(0x3F803F80u, 0x3F803F80u, 0x3F803F80u, 0x3F803F80u);
        uint4* dst = reinterpret_cast<uint4*>(smem + P2_ONES);
#pragma unroll
        for (int i = 0; i < 4; i++) dst[tid + i * 512] = ones;
        fence_proxy_async();
    }
    __syncthreads();
    pdl_launch();
    pdl_wait();
    if (tid == 0) {
        const uint8_t* gk = reinterpret_cast<const uint8_t*>(g_k) + (size_t)head * 65536;
        const uint8_t* gv = reinterpret_cast<const uint8_t*>(g_v) + (size_t)head * 65536;
        for (int i = 0; i < P2_NCH; i++) {
            uint32_t b = bar_kv + 8 * i;
            mbar_expect_tx(b, 16384);
            bulk_load(sb + P2_K + i * 8192, gk + i * 8192, 8192, b);
            bulk_load(sb + P2_V + i * 4096, gv + i * 4096, 4096, b);
            bulk_load(sb + P2_V + 32768 + i * 4096, gv + 32768 + i * 4096, 4096, b);
        }
    }
    const int wg = warp >> 2, wq = warp & 3;
    uint32_t qf[2][4];
#pragma unroll
    for (int ti = 0; ti < 2; ti++) {
        const int rg = (qq * 512 + wg * 128 + ti * 64 + wq * 16) >> 3;
        const uint32_t* src = g_q + ((head * 256 + rg) * 2) * 32 + lane;
        qf[ti][0] = src[0]; qf[ti][2] = src[32]; qf[ti][1] = src[64]; qf[ti][3] = src[96];
    }
    bool fast;
    {
        uint32_t kmax = 0, vmax = 0;
        if (tid < 128) {
            float2 kv = g_kv[head * 128 + tid];
            kmax = __reduce_max_sync(0xffffffffu, __float_as_uint(kv.x));
            vmax = __reduce_max_sync(0xffffffffu, __float_as_uint(kv.y));
            if (lane == 0) { s_red[warp * 2] = kmax; s_red[warp * 2 + 1] = vmax; }
        }
        float qn = 0.f;
#pragma unroll
        for (int ti = 0; ti < 2; ti++) {
            float a = bf_lo(qf[ti][0]) * bf_lo(qf[ti][0]) + bf_hi(qf[ti][0]) * bf_hi(qf[ti][0]) +
                      bf_lo(qf[ti][2]) * bf_lo(qf[ti][2]) + bf_hi(qf[ti][2]) * bf_hi(qf[ti][2]);
            float b = bf_lo(qf[ti][1]) * bf_lo(qf[ti][1]) + bf_hi(qf[ti][1]) * bf_hi(qf[ti][1]) +
                      bf_lo(qf[ti][3]) * bf_lo(qf[ti][3]) + bf_hi(qf[ti][3]) * bf_hi(qf[ti][3]);
            a += __shfl_xor_sync(0xffffffffu, a, 1); b += __shfl_xor_sync(0xffffffffu, b, 1);
            a += __shfl_xor_sync(0xffffffffu, a, 2); b += __shfl_xor_sync(0xffffffffu, b, 2);
            qn = __uint_as_float(max(__float_as_uint(qn), max(__float_as_uint(fabsf(a)), __float_as_uint(fabsf(b)))));
        }
        __syncthreads();
        kmax = max(max(s_red[0], s_red[2]), max(s_red[4], s_red[6]));
        vmax = max(max(s_red[1], s_red[3]), max(s_red[5], s_red[7]));
        bool ok = (qn * __uint_as_float(kmax) <= 4096.f) && (__uint_as_float(vmax) <= 1.0995116e12f);
        fast = __syncthreads_and(ok);
    }
    const uint64_t dk = make_desc(sb + P2_K, 128, 256, 0);
    const uint64_t dv = make_desc(sb + P2_V, 128, 32768, 0);
#pragma unroll 1
    for (int ti = 0; ti < 2; ti++) {
        uint32_t q[4];
#pragma unroll
        for (int i = 0; i < 4; i++) q[i] = ti == 0 ? qf[0][i] : qf[1][i];
        float o[12];
#pragma unroll
        for (int i = 0; i < 12; i++) o[i] = 0.f;
        uint32_t p[16];
        float s0[32];
        if (fast) {
            float s1[32];
            if (ti == 0) mbar_wait(bar_kv, 0);
            wg_fence();
            wgmma_rs_n64_z(s0, q[0], q[1], q[2], q[3], dk);
            wg_commit();
            wg_commit();
#pragma unroll 1
            for (int j = 0; j < 32; j += 2) {
                attn_step(s0, s1, p, o, q, dk, dv, j, ti == 0, bar_kv);
                attn_step(s1, s0, p, o, q, dk, dv, j + 1, ti == 0, bar_kv);
            }
            wg_wait<0>();
            reg_fence(o);
        } else {
            float m0 = -INFINITY, m1 = -INFINITY;
#pragma unroll 1
            for (int j = 0; j < 32; j++) {
                if (ti == 0 && (j & 3) == 0) mbar_wait(bar_kv + 8 * (j >> 2), 0);
                wg_fence();
                wgmma_rs_n64_z(s0, q[0], q[1], q[2], q[3], dk + (uint64_t)j * 128);
                wg_commit();
                wg_wait<0>();
                reg_fence(s0);
                reg_fence(o);
                float x0 = m0, x1 = m1;
#pragma unroll
                for (int i = 0; i < 8; i++) {
                    x0 = fmaxf(x0, fmaxf(s0[4 * i], s0[4 * i + 1]));
                    x1 = fmaxf(x1, fmaxf(s0[4 * i + 2], s0[4 * i + 3]));
                }
                x0 = fmaxf(x0, __shfl_xor_sync(0xffffffffu, x0, 1)); x1 = fmaxf(x1, __shfl_xor_sync(0xffffffffu, x1, 1));
                x0 = fmaxf(x0, __shfl_xor_sync(0xffffffffu, x0, 2)); x1 = fmaxf(x1, __shfl_xor_sync(0xffffffffu, x1, 2));
                float a0 = ex2(m0 - x0), a1 = ex2(m1 - x1);
                m0 = x0; m1 = x1;
#pragma unroll
                for (int i = 0; i < 3; i++) { o[4 * i] *= a0; o[4 * i + 1] *= a0; o[4 * i + 2] *= a1; o[4 * i + 3] *= a1; }
#pragma unroll
                for (int i = 0; i < 8; i++) {
                    p[2 * i] = pack_bf16(ex2(s0[4 * i] - m0), ex2(s0[4 * i + 1] - m0));
                    p[2 * i + 1] = pack_bf16(ex2(s0[4 * i + 2] - m1), ex2(s0[4 * i + 3] - m1));
                }
                wg_fence();
#pragma unroll
                for (int t = 0; t < 4; t++)
                    wgmma_rs_n24_t(o, p[4 * t], p[4 * t + 1], p[4 * t + 2], p[4 * t + 3], dv + (uint64_t)(j * 4 + t) * 16);
                wg_commit();
                wg_wait<0>();
                reg_fence(o);
            }
        }
        const float i0 = 1.f / o[8], i1 = 1.f / o[10];
        const int row = qq * 512 + wg * 128 + ti * 64 + wq * 16;
        uint32_t* dst = g_o + (((row >> 7) * 64 + head * 2) * 16 + ((row & 127) >> 3)) * 32 + lane;
        dst[0] = pack_bf16(o[0] * i0, o[1] * i0);
        dst[32] = pack_bf16(o[2] * i1, o[3] * i1);
        dst[512] = pack_bf16(o[4] * i0, o[5] * i0);
        dst[544] = pack_bf16(o[6] * i1, o[7] * i1);
    }
}

constexpr int P3_A = 0, P3_B = 131072, P3_AUX = 196608;
constexpr int P3_SMEM = P3_AUX + 128;
__global__ void __launch_bounds__(288, 1)
k_oproj(const __grid_constant__ CUtensorMap tm_wo, const __nv_bfloat16* __restrict__ x) {
    extern __shared__ __align__(1024) uint8_t smem[];
    const uint32_t sb = smem_u32(smem);
    const uint32_t bar_a = sb + P3_AUX, bar_b = bar_a + 64;
    const int tid = threadIdx.x, warp = tid >> 5, lane = tid & 31;
    const int rb = blockIdx.x >> 3, c = blockIdx.x & 7;
    if (tid == 0) {
        if (sb & 1023) asm volatile("trap;");
        for (int i = 0; i < 8; i++) mbar_init(bar_a + 8 * i, 1);
        mbar_init(bar_b, 1); mbar_init(bar_b + 8, 1);
        fence_mbar_init();
    }
    __syncthreads();
    pdl_launch();
    if (warp == 8) {
        if (lane == 0) {
            mbar_expect_tx(bar_b, 32768);
            tma_load_2d(sb + P3_B, &tm_wo, c * 64, 0, bar_b);
            mbar_expect_tx(bar_b + 8, 32768);
            tma_load_2d(sb + P3_B + 32768, &tm_wo, c * 64, 256, bar_b + 8);
            pdl_wait();
            const uint8_t* src = reinterpret_cast<const uint8_t*>(g_o) + (size_t)rb * 131072;
            for (int i = 0; i < 8; i++) {
                mbar_expect_tx(bar_a + 8 * i, 16384);
                bulk_load(sb + P3_A + i * 16384, src + i * 16384, 16384, bar_a + 8 * i);
            }
        }
    } else {
        const int wg = warp >> 2, q4 = lane & 3;
        const int r0 = rb * 128 + warp * 16 + (lane >> 2);
        uint32_t xr[16];
        const uint32_t* xp = reinterpret_cast<const uint32_t*>(x + (size_t)r0 * DM + c * 64 + q4 * 2);
#pragma unroll
        for (int j = 0; j < 8; j++) { xr[2 * j] = __ldg(xp + j * 4); xr[2 * j + 1] = __ldg(xp + 8 * (DM / 2) + j * 4); }
        float acc[32];
        const uint64_t da = make_desc(sb + P3_A + wg * 1024, 2048, 128, 0);
        const uint64_t db = make_desc(sb + P3_B, 8192, 1024, 1);
        for (int kb = 0; kb < 8; kb++) {
            if ((kb & 3) == 0) mbar_wait(bar_b + 8 * (kb >> 2), 0);
            mbar_wait(bar_a + 8 * kb, 0);
            wg_fence();
#pragma unroll
            for (int k = 0; k < 4; k++) wgmma_ss_n64_t(acc, da + (kb * 4 + k) * 256, db + (kb * 4 + k) * 128, kb | k);
            wg_commit();
        }
        wg_wait<0>();
        reg_fence(acc);
        pdl_wait();
        float s0 = 0.f, q0 = 0.f, s1 = 0.f, q1 = 0.f;
        uint32_t* dst = g_h + ((rb * 64 + c * 8) * 16 + warp * 2) * 32 + lane;
#pragma unroll
        for (int j = 0; j < 8; j++) {
            uint32_t p0 = pack_bf16(acc[4 * j] + bf_lo(xr[2 * j]), acc[4 * j + 1] + bf_hi(xr[2 * j]));
            uint32_t p1 = pack_bf16(acc[4 * j + 2] + bf_lo(xr[2 * j + 1]), acc[4 * j + 3] + bf_hi(xr[2 * j + 1]));
            dst[j * 512] = p0;
            dst[j * 512 + 32] = p1;
            float a = bf_lo(p0), b = bf_hi(p0), e = bf_lo(p1), f = bf_hi(p1);
            s0 += a + b; q0 = fmaf(a, a, fmaf(b, b, q0));
            s1 += e + f; q1 = fmaf(e, e, fmaf(f, f, q1));
        }
        s0 += __shfl_xor_sync(0xffffffffu, s0, 1); q0 += __shfl_xor_sync(0xffffffffu, q0, 1);
        s1 += __shfl_xor_sync(0xffffffffu, s1, 1); q1 += __shfl_xor_sync(0xffffffffu, q1, 1);
        s0 += __shfl_xor_sync(0xffffffffu, s0, 2); q0 += __shfl_xor_sync(0xffffffffu, q0, 2);
        s1 += __shfl_xor_sync(0xffffffffu, s1, 2); q1 += __shfl_xor_sync(0xffffffffu, q1, 2);
        if (q4 == 0) {
            g_hstat[r0 * 8 + c] = make_float2(s0, q0);
            g_hstat[(r0 + 8) * 8 + c] = make_float2(s1, q1);
        } else if (q4 == 1) {
            g_zstat[r0 * 8 + c] = make_float2(0.f, -1.f);
            g_zstat[(r0 + 8) * 8 + c] = make_float2(0.f, -1.f);
        }
    }
}

constexpr int P4_STAGES = 6;
constexpr int P4_A = 0, P4_B = 131072, P4_AUX = P4_B + P4_STAGES * 16384;
constexpr int P4_SMEM = P4_AUX + 256;
__global__ void __launch_bounds__(544, 1)
k_win(const __grid_constant__ CUtensorMap tm_win) {
    extern __shared__ __align__(1024) uint8_t smem[];
    const uint32_t sb = smem_u32(smem);
    const uint32_t bar_a = sb + P4_AUX, bar_full = bar_a + 64, bar_empty = bar_full + 8 * P4_STAGES;
    const int tid = threadIdx.x, warp = tid >> 5, lane = tid & 31;
    const int rb = blockIdx.x >> 3, c = blockIdx.x & 7;
    if (tid == 0) {
        if (sb & 1023) asm volatile("trap;");
        for (int i = 0; i < 8; i++) mbar_init(bar_a + 8 * i, 1);
        for (int i = 0; i < P4_STAGES; i++) { mbar_init(bar_full + 8 * i, 1); mbar_init(bar_empty + 8 * i, 8); }
        fence_mbar_init();
    }
    __syncthreads();
    pdl_launch();
    if (warp == 16) {
        if (lane == 0) {
            for (int i = 0; i < 16; i++) {
                int s = i % P4_STAGES;
                if (i == P4_STAGES) {
                    pdl_wait();
                    const uint8_t* src = reinterpret_cast<const uint8_t*>(g_h) + (size_t)rb * 131072;
                    for (int a = 0; a < 8; a++) {
                        mbar_expect_tx(bar_a + 8 * a, 16384);
                        bulk_load(sb + P4_A + a * 16384, src + a * 16384, 16384, bar_a + 8 * a);
                    }
                }
                if (i >= P4_STAGES) mbar_wait(bar_empty + 8 * s, ((i / P4_STAGES) - 1) & 1);
                const int col = (i < 8 ? FH : 0) + c * 112, kb = i & 7;
                uint32_t st = sb + P4_B + s * 16384, fb = bar_full + 8 * s;
                mbar_expect_tx(fb, 16384);
                tma_load_2d(st, &tm_win, col, kb * 64, fb);
                tma_load_2d(st + 8192, &tm_win, col + 64, kb * 64, fb);
            }
        }
    } else {
        const int wg = warp >> 2, part = wg >> 1, wm = wg & 1, w8 = warp & 7, q4 = lane & 3;
        const int r0 = rb * 128 + w8 * 16 + (lane >> 2);
        pdl_wait();
        float mean0, rstd0, mean1, rstd1;
        {
            float4 a = *reinterpret_cast<const float4*>(&g_hstat[r0 * 8 + q4 * 2]);
            float4 b = *reinterpret_cast<const float4*>(&g_hstat[(r0 + 8) * 8 + q4 * 2]);
            float s0 = a.x + a.z, q0 = a.y + a.w, s1 = b.x + b.z, q1 = b.y + b.w;
            s0 += __shfl_xor_sync(0xffffffffu, s0, 1); q0 += __shfl_xor_sync(0xffffffffu, q0, 1);
            s1 += __shfl_xor_sync(0xffffffffu, s1, 1); q1 += __shfl_xor_sync(0xffffffffu, q1, 1);
            s0 += __shfl_xor_sync(0xffffffffu, s0, 2); q0 += __shfl_xor_sync(0xffffffffu, q0, 2);
            s1 += __shfl_xor_sync(0xffffffffu, s1, 2); q1 += __shfl_xor_sync(0xffffffffu, q1, 2);
            mean0 = s0 * (1.f / DM); mean1 = s1 * (1.f / DM);
            rstd0 = rsqrtf(fmaxf(q0 * (1.f / DM) - mean0 * mean0, 0.f) + LN_EPS);
            rstd1 = rsqrtf(fmaxf(q1 * (1.f / DM) - mean1 * mean1, 0.f) + LN_EPS);
        }
        float acc[56];
        const uint64_t da = make_desc(sb + P4_A + wm * 1024, 2048, 128, 0);
        if (part == 1) bar_sync(1, 512);
        for (int kb = 0; kb < 8; kb++) {
            const int i = part * 8 + kb, s = i % P4_STAGES;
            if (part == 0) mbar_wait(bar_a + 8 * kb, 0);
            mbar_wait(bar_full + 8 * s, (i / P4_STAGES) & 1);
            const uint64_t db = make_desc(sb + P4_B + s * 16384, 8192, 1024, 1);
            wg_fence();
#pragma unroll
            for (int k = 0; k < 4; k++) wgmma_ss_n112_t(acc, da + (kb * 4 + k) * 256, db + k * 128, kb | k);
            wg_commit();
            if (kb > 0) {
                wg_wait<1>();
                if (lane == 0) mbar_arrive(bar_empty + 8 * ((i - 1) % P4_STAGES));
            }
        }
        if (part == 0) bar_arrive(1, 512);
        wg_wait<0>();
        reg_fence(acc);
        if (lane == 0) mbar_arrive(bar_empty + 8 * ((part * 8 + 7) % P4_STAGES));
        const float* cs = g_csin + (part == 0 ? FH : 0) + c * 112 + q4 * 2;
        uint32_t z[28];
        float s0 = 0.f, q0 = 0.f, s1 = 0.f, q1 = 0.f;
#pragma unroll
        for (int j = 0; j < 14; j++) {
            float2 cv = *reinterpret_cast<const float2*>(cs + j * 8);
            float v0 = gelu_tanh(rstd0 * fmaf(-mean0, cv.x, acc[4 * j]));
            float v1 = gelu_tanh(rstd0 * fmaf(-mean0, cv.y, acc[4 * j + 1]));
            float v2 = gelu_tanh(rstd1 * fmaf(-mean1, cv.x, acc[4 * j + 2]));
            float v3 = gelu_tanh(rstd1 * fmaf(-mean1, cv.y, acc[4 * j + 3]));
            uint32_t p0 = pack_bf16(v0, v1), p1 = pack_bf16(v2, v3);
            z[2 * j] = p0; z[2 * j + 1] = p1;
            float a = bf_lo(p0), b = bf_hi(p0), e = bf_lo(p1), f = bf_hi(p1);
            s0 += a + b; q0 = fmaf(a, a, fmaf(b, b, q0));
            s1 += e + f; q1 = fmaf(e, e, fmaf(f, f, q1));
        }
        if (part == 1) {
            uint4* dst = g_z1 + (size_t)(((rb * 8 + c) * 2 + wm) * 7) * 128 + (tid & 127);
#pragma unroll
            for (int j = 0; j < 7; j++) dst[j * 128] = make_uint4(z[4 * j], z[4 * j + 1], z[4 * j + 2], z[4 * j + 3]);
        } else {
            s0 += __shfl_xor_sync(0xffffffffu, s0, 1); q0 += __shfl_xor_sync(0xffffffffu, q0, 1);
            s1 += __shfl_xor_sync(0xffffffffu, s1, 1); q1 += __shfl_xor_sync(0xffffffffu, q1, 1);
            s0 += __shfl_xor_sync(0xffffffffu, s0, 2); q0 += __shfl_xor_sync(0xffffffffu, q0, 2);
            s1 += __shfl_xor_sync(0xffffffffu, s1, 2); q1 += __shfl_xor_sync(0xffffffffu, q1, 2);
            if (q4 < 2) {
                float2* p = &g_zstat[(r0 + q4 * 8) * 8 + c];
                float ss = q4 == 0 ? s0 : s1, qq = q4 == 0 ? q0 : q1;
                asm volatile("st.relaxed.gpu.global.v2.f32 [%0], {%1, %2};" ::"l"(p), "f"(ss), "f"(qq) : "memory");
            }
            float4 a, b;
            const float2* pa = &g_zstat[r0 * 8 + q4 * 2];
            const float2* pb = &g_zstat[(r0 + 8) * 8 + q4 * 2];
            long long t0 = clock64();
            while (true) {
                asm volatile("ld.relaxed.gpu.global.v2.f32 {%0,%1}, [%2];" : "=f"(a.x), "=f"(a.y) : "l"(pa) : "memory");
                asm volatile("ld.relaxed.gpu.global.v2.f32 {%0,%1}, [%2];" : "=f"(a.z), "=f"(a.w) : "l"(pa + 1) : "memory");
                asm volatile("ld.relaxed.gpu.global.v2.f32 {%0,%1}, [%2];" : "=f"(b.x), "=f"(b.y) : "l"(pb) : "memory");
                asm volatile("ld.relaxed.gpu.global.v2.f32 {%0,%1}, [%2];" : "=f"(b.z), "=f"(b.w) : "l"(pb + 1) : "memory");
                bool bad = (a.y < 0.f) || (a.w < 0.f) || (b.y < 0.f) || (b.w < 0.f);
                if (!__any_sync(0xffffffffu, bad)) break;
                if (clock64() - t0 > 2000000000LL) asm volatile("trap;");
                __nanosleep(64);
            }
            s0 = a.x + a.z; q0 = a.y + a.w; s1 = b.x + b.z; q1 = b.y + b.w;
            s0 += __shfl_xor_sync(0xffffffffu, s0, 1); q0 += __shfl_xor_sync(0xffffffffu, q0, 1);
            s1 += __shfl_xor_sync(0xffffffffu, s1, 1); q1 += __shfl_xor_sync(0xffffffffu, q1, 1);
            s0 += __shfl_xor_sync(0xffffffffu, s0, 2); q0 += __shfl_xor_sync(0xffffffffu, q0, 2);
            s1 += __shfl_xor_sync(0xffffffffu, s1, 2); q1 += __shfl_xor_sync(0xffffffffu, q1, 2);
            const float mu0 = s0 * (1.f / FH), mu1 = s1 * (1.f / FH);
            const float rr0 = rsqrtf(fmaxf(q0 * (1.f / FH) - mu0 * mu0, 0.f) + LN_EPS);
            const float rr1 = rsqrtf(fmaxf(q1 * (1.f / FH) - mu1 * mu1, 0.f) + LN_EPS);
            uint32_t* dst = g_z2 + ((c * 256 + rb * 16 + w8 * 2) * 14) * 32 + lane;
#pragma unroll
            for (int j = 0; j < 14; j++) {
                dst[j * 32] = pack_bf16((bf_lo(z[2 * j]) - mu0) * rr0, (bf_hi(z[2 * j]) - mu0) * rr0);
                dst[(14 + j) * 32] = pack_bf16((bf_lo(z[2 * j + 1]) - mu1) * rr1, (bf_hi(z[2 * j + 1]) - mu1) * rr1);
            }
        }
    }
}

constexpr int P5_AS = 8, P5_BS = 6;
constexpr int P5_A = 0, P5_B = P5_AS * 16384, P5_AUX = P5_B + P5_BS * 14336;
constexpr int P5_SMEM = P5_AUX + 256;
__global__ void __launch_bounds__(320, 1)
k_sp(const __grid_constant__ CUtensorMap tm_wsp, const __nv_bfloat16* __restrict__ b_sp) {
    extern __shared__ __align__(1024) uint8_t smem[];
    const uint32_t sb = smem_u32(smem);
    const uint32_t bar_af = sb + P5_AUX, bar_ae = bar_af + 8 * P5_AS, bar_bf = bar_ae + 8 * P5_AS, bar_be = bar_bf + 8 * P5_BS;
    const int tid = threadIdx.x, warp = tid >> 5, lane = tid & 31;
    const int rb = blockIdx.x >> 3, c = blockIdx.x & 7;
    if (tid == 0) {
        if (sb & 1023) asm volatile("trap;");
        for (int i = 0; i < P5_AS; i++) { mbar_init(bar_af + 8 * i, 1); mbar_init(bar_ae + 8 * i, 8); }
        for (int i = 0; i < P5_BS; i++) { mbar_init(bar_bf + 8 * i, 1); mbar_init(bar_be + 8 * i, 8); }
        fence_mbar_init();
    }
    __syncthreads();
    pdl_launch();
    if (warp == 8) {
        if (lane == 0) {
            for (int i = 0; i < 32; i++) {
                int s = i % P5_AS;
                if (i >= P5_AS) mbar_wait(bar_ae + 8 * s, ((i / P5_AS) - 1) & 1);
                mbar_expect_tx(bar_af + 8 * s, 16384);
                tma_load_2d(sb + P5_A + s * 16384, &tm_wsp, i * 64, rb * 128, bar_af + 8 * s);
            }
        }
    } else if (warp == 9) {
        if (lane == 0) {
            pdl_wait();
            const uint8_t* src = reinterpret_cast<const uint8_t*>(g_z2) + (size_t)c * (256 * 14 * 128);
            for (int i = 0; i < 32; i++) {
                int s = i % P5_BS;
                if (i >= P5_BS) mbar_wait(bar_be + 8 * s, ((i / P5_BS) - 1) & 1);
                mbar_expect_tx(bar_bf + 8 * s, 14336);
                bulk_load(sb + P5_B + s * 14336, src + (size_t)i * 14336, 14336, bar_bf + 8 * s);
            }
        }
    } else {
        const int wg = warp >> 2;
        const int r0 = rb * 128 + warp * 16 + (lane >> 2);
        const float bias0 = __bfloat162float(b_sp[r0]), bias1 = __bfloat162float(b_sp[r0 + 8]);
        pdl_wait();
        uint4 z1[7];
        {
            const uint4* src = g_z1 + (size_t)(((rb * 8 + c) * 2 + wg) * 7) * 128 + (tid & 127);
#pragma unroll
            for (int j = 0; j < 7; j++) z1[j] = src[j * 128];
        }
        float acc[56];
        for (int kb = 0; kb < 32; kb++) {
            const int sa = kb % P5_AS, sbi = kb % P5_BS;
            mbar_wait(bar_af + 8 * sa, (kb / P5_AS) & 1);
            mbar_wait(bar_bf + 8 * sbi, (kb / P5_BS) & 1);
            const uint64_t da = make_desc(sb + P5_A + sa * 16384 + wg * 8192, 16, 1024, 1);
            const uint64_t db = make_desc(sb + P5_B + sbi * 14336, 1792, 128, 0);
            wg_fence();
#pragma unroll
            for (int k = 0; k < 4; k++) wgmma_ss_n112_t(acc, da + k * 2, db + k * 224, kb | k);
            wg_commit();
            if (kb > 0) {
                wg_wait<1>();
                if (lane == 0) { mbar_arrive(bar_ae + 8 * ((kb - 1) % P5_AS)); mbar_arrive(bar_be + 8 * ((kb - 1) % P5_BS)); }
            }
        }
        wg_wait<0>();
        reg_fence(acc);
        uint32_t* dst = g_u + ((rb * 112 + c * 14) * 16 + warp * 2) * 32 + lane;
#pragma unroll
        for (int j = 0; j < 14; j++) {
            uint32_t za = (j & 1) ? z1[j >> 1].z : z1[j >> 1].x, zb = (j & 1) ? z1[j >> 1].w : z1[j >> 1].y;
            dst[j * 512] = pack_bf16(bf_lo(za) * (acc[4 * j] + bias0), bf_hi(za) * (acc[4 * j + 1] + bias0));
            dst[j * 512 + 32] = pack_bf16(bf_lo(zb) * (acc[4 * j + 2] + bias1), bf_hi(zb) * (acc[4 * j + 3] + bias1));
        }
    }
}

constexpr int P6_AS = 4;
constexpr int P6_A = 0, P6_B = P6_AS * 28672, P6_AUX = P6_B + 8 * 14336;
constexpr int P6_SMEM = P6_AUX + 256;
__global__ void __launch_bounds__(288, 1)
k_wout(const __grid_constant__ CUtensorMap tm_wout, const __grid_constant__ CUtensorMap tm_out) {
    extern __shared__ __align__(1024) uint8_t smem[];
    const uint32_t sb = smem_u32(smem);
    const uint32_t bar_af = sb + P6_AUX, bar_ae = bar_af + 8 * P6_AS, bar_b = bar_ae + 8 * P6_AS;
    const int tid = threadIdx.x, warp = tid >> 5, lane = tid & 31;
    const int rb = blockIdx.x >> 3, c = blockIdx.x & 7;
    if (tid == 0) {
        if (sb & 1023) asm volatile("trap;");
        for (int i = 0; i < P6_AS; i++) { mbar_init(bar_af + 8 * i, 1); mbar_init(bar_ae + 8 * i, 8); }
        for (int i = 0; i < 8; i++) mbar_init(bar_b + 8 * i, 1);
        fence_mbar_init();
    }
    __syncthreads();
    if (warp == 8) {
        if (lane == 0) {
            for (int i = 0; i < 8; i++) {
                mbar_expect_tx(bar_b + 8 * i, 14336);
                tma_load_2d(sb + P6_B + i * 14336, &tm_wout, c * 64, i * 112, bar_b + 8 * i);
            }
            pdl_wait();
            const uint8_t* src = reinterpret_cast<const uint8_t*>(g_u) + (size_t)rb * (112 * 16 * 128);
            for (int i = 0; i < 8; i++) {
                int s = i % P6_AS;
                if (i >= P6_AS) mbar_wait(bar_ae + 8 * s, 0);
                mbar_expect_tx(bar_af + 8 * s, 28672);
                bulk_load(sb + P6_A + s * 28672, src + (size_t)i * 28672, 28672, bar_af + 8 * s);
            }
        }
    } else {
        const int wg = warp >> 2;
        pdl_wait();
        uint32_t hr[16];
        {
            const uint32_t* src = g_h + ((rb * 64 + c * 8) * 16 + warp * 2) * 32 + lane;
#pragma unroll
            for (int j = 0; j < 8; j++) { hr[2 * j] = src[j * 512]; hr[2 * j + 1] = src[j * 512 + 32]; }
        }
        float acc[32];
        for (int kb = 0; kb < 8; kb++) {
            const int s = kb % P6_AS;
            mbar_wait(bar_b + 8 * kb, 0);
            mbar_wait(bar_af + 8 * s, (kb / P6_AS) & 1);
            const uint64_t da = make_desc(sb + P6_A + s * 28672 + wg * 1024, 2048, 128, 0);
            const uint64_t db = make_desc(sb + P6_B + kb * 14336, 8192, 1024, 1);
            wg_fence();
#pragma unroll
            for (int k = 0; k < 7; k++) wgmma_ss_n64_t(acc, da + k * 256, db + k * 128, kb | k);
            wg_commit();
            if (kb > 0) {
                wg_wait<1>();
                if (lane == 0) mbar_arrive(bar_ae + 8 * ((kb - 1) % P6_AS));
            }
        }
        wg_wait<0>();
        reg_fence(acc);
        bar_sync(1, 256);
        const uint32_t so = sb + P6_B + warp * 2048;
#pragma unroll
        for (int jp = 0; jp < 4; jp++) {
            uint32_t r[4];
#pragma unroll
            for (int e = 0; e < 2; e++) {
                const int j = jp * 2 + e;
                r[2 * e] = pack_bf16(acc[4 * j] + bf_lo(hr[2 * j]), acc[4 * j + 1] + bf_hi(hr[2 * j]));
                r[2 * e + 1] = pack_bf16(acc[4 * j + 2] + bf_lo(hr[2 * j + 1]), acc[4 * j + 3] + bf_hi(hr[2 * j + 1]));
            }
            const int mt = lane >> 3, rr = (lane & 7) + (mt & 1) * 8, chn = jp * 2 + (mt >> 1);
            const uint32_t addr = so + rr * 128 + ((chn ^ (rr & 7)) << 4);
            asm volatile("stmatrix.sync.aligned.m8n8.x4.shared.b16 [%0], {%1,%2,%3,%4};" ::"r"(addr), "r"(r[0]), "r"(r[1]), "r"(r[2]), "r"(r[3]) : "memory");
        }
        fence_proxy_async();
        bar_sync(1, 256);
        if (tid == 0) {
            tma_store_2d(&tm_out, sb + P6_B, c * 64, rb * 128);
            asm volatile("cp.async.bulk.commit_group;" ::: "memory");
            asm volatile("cp.async.bulk.wait_group.read 0;" ::: "memory");
        }
    }
}

typedef CUresult (*EncodeFn)(CUtensorMap*, CUtensorMapDataType, cuuint32_t, void*, const cuuint64_t*, const cuuint64_t*,
                             const cuuint32_t*, const cuuint32_t*, CUtensorMapInterleave, CUtensorMapSwizzle,
                             CUtensorMapL2promotion, CUtensorMapFloatOOBfill);

void make_map(EncodeFn fn, CUtensorMap* tm, const void* ptr, uint64_t inner, uint64_t outer, uint32_t bi, uint32_t bo) {
    cuuint64_t dims[2] = {inner, outer};
    cuuint64_t strides[1] = {inner * 2};
    cuuint32_t box[2] = {bi, bo};
    cuuint32_t es[2] = {1, 1};
    fn(tm, CU_TENSOR_MAP_DATA_TYPE_BFLOAT16, 2, const_cast<void*>(ptr), dims, strides, box, es, CU_TENSOR_MAP_INTERLEAVE_NONE,
       CU_TENSOR_MAP_SWIZZLE_128B, CU_TENSOR_MAP_L2_PROMOTION_L2_256B, CU_TENSOR_MAP_FLOAT_OOB_FILL_NONE);
}

template <typename... KArgs, typename... Args>
void launch(void (*kern)(KArgs...), int grid, int block, int smem, bool pdl, Args... args) {
    cudaLaunchConfig_t cfg = {};
    cfg.gridDim = dim3(grid); cfg.blockDim = dim3(block); cfg.dynamicSmemBytes = smem; cfg.stream = cudaStreamPerThread;
    cudaLaunchAttribute at[1];
    at[0].id = cudaLaunchAttributeProgrammaticStreamSerialization;
    at[0].val.programmaticStreamSerializationAllowed = 1;
    cfg.attrs = at; cfg.numAttrs = pdl ? 1 : 0;
    cudaLaunchKernelEx(&cfg, kern, KArgs(args)...);
}

}

extern "C" void kernel_launch(void* const* d_in, const int* in_sizes, int n_in, void* d_out, int out_size) {
    (void)in_sizes; (void)n_in; (void)out_size;
    const __nv_bfloat16* x = (const __nv_bfloat16*)d_in[0];
    const __nv_bfloat16* wqkv = (const __nv_bfloat16*)d_in[1];
    const __nv_bfloat16* wo = (const __nv_bfloat16*)d_in[2];
    const __nv_bfloat16* w_in = (const __nv_bfloat16*)d_in[4];
    const __nv_bfloat16* w_sp = (const __nv_bfloat16*)d_in[5];
    const __nv_bfloat16* b_sp = (const __nv_bfloat16*)d_in[6];
    const __nv_bfloat16* w_out = (const __nv_bfloat16*)d_in[7];

    static EncodeFn enc = nullptr;
    if (!enc) {
        void* fp = nullptr;
        cudaDriverEntryPointQueryResult qr;
        cudaGetDriverEntryPoint("cuTensorMapEncodeTiled", &fp, cudaEnableDefault, &qr);
        enc = (EncodeFn)fp;
        cudaFuncSetAttribute(k_qkv, cudaFuncAttributeMaxDynamicSharedMemorySize, P1_SMEM);
        cudaFuncSetAttribute(k_attn, cudaFuncAttributeMaxDynamicSharedMemorySize, P2_SMEM);
        cudaFuncSetAttribute(k_oproj, cudaFuncAttributeMaxDynamicSharedMemorySize, P3_SMEM);
        cudaFuncSetAttribute(k_win, cudaFuncAttributeMaxDynamicSharedMemorySize, P4_SMEM);
        cudaFuncSetAttribute(k_sp, cudaFuncAttributeMaxDynamicSharedMemorySize, P5_SMEM);
        cudaFuncSetAttribute(k_wout, cudaFuncAttributeMaxDynamicSharedMemorySize, P6_SMEM);
    }
    CUtensorMap tm_x, tm_wqkv, tm_wo, tm_win, tm_wsp, tm_wout, tm_out;
    make_map(enc, &tm_x, x, DM, SEQ, 64, 128);
    make_map(enc, &tm_wqkv, wqkv, 3 * DM, DM, 64, 64);
    make_map(enc, &tm_wo, wo, DM, DM, 64, 256);
    make_map(enc, &tm_win, w_in, FF, DM, 64, 64);
    make_map(enc, &tm_wsp, w_sp, SEQ, SEQ, 64, 128);
    make_map(enc, &tm_wout, w_out, DM, FH, 64, 112);
    make_map(enc, &tm_out, d_out, DM, SEQ, 64, 128);

    launch(k_qkv, 128, 416, P1_SMEM, false, tm_x, tm_wqkv);
    launch(k_attn, 132, 512, P2_SMEM, true, w_in, wo, w_sp, w_out);
    launch(k_oproj, 128, 288, P3_SMEM, true, tm_wo, x);
    launch(k_win, 128, 544, P4_SMEM, true, tm_win);
    launch(k_sp, 128, 320, P5_SMEM, true, tm_wsp, b_sp);
    launch(k_wout, 128, 288, P6_SMEM, true, tm_wout, tm_out);
}
```

```cpp
#include <cuda_runtime.h>
#include <cuda_bf16.h>
#include <cuda.h>
#include <stdint.h>

namespace {

constexpr int SEQ = 2048, DM = 512, NH = 32, FF = 1792, FH = 896;
constexpr float LN_EPS = 1e-5f;

__device__ __align__(1024) uint32_t g_q[NH * SEQ * 8];
__device__ __align__(1024) uint32_t g_k[NH * SEQ * 8];
__device__ __align__(1024) uint32_t g_v[NH * SEQ * 8];
__device__ __align__(16) float2 g_kv[NH * 128];
__device__ __align__(16) float g_qn[NH * 128];
__device__ __align__(1024) uint32_t g_o[SEQ * DM / 2];
__device__ __align__(1024) uint32_t g_h[SEQ * DM / 2];
__device__ __align__(128) float2 g_hstat[SEQ * 8];
__device__ __align__(128) float2 g_zstat[SEQ * 8];
__device__ __align__(16) float g_csin[FF];
__device__ __align__(1024) uint4 g_win[DM * FF / 8];
__device__ __align__(1024) uint32_t g_z2[SEQ * FH / 2];
__device__ __align__(128) uint32_t g_flag[8 * 128];
__device__ __align__(1024) uint32_t g_u[SEQ * FH / 2];
__device__ __align__(16) uint32_t g_xst[128 * 256];
__device__ __align__(16) uint32_t g_wcs[128 * 192];
__device__ uint32_t g_role[1024];
__device__ uint32_t g_cnt[8];

#define TSP(k, s)
#define TS(k, s)
#define TS0(k, s)
__device__ __forceinline__ uint32_t smem_u32(const void* p) { return (uint32_t)__cvta_generic_to_shared(p); }
__device__ __forceinline__ void mbar_init(uint32_t bar, uint32_t cnt) {
    asm volatile("mbarrier.init.shared::cta.b64 [%0], %1;" ::"r"(bar), "r"(cnt) : "memory");
}
__device__ __forceinline__ void mbar_expect_tx(uint32_t bar, uint32_t bytes) {
    asm volatile("mbarrier.arrive.expect_tx.shared::cta.b64 _, [%0], %1;" ::"r"(bar), "r"(bytes) : "memory");
}
__device__ __forceinline__ void mbar_arrive(uint32_t bar) {
    asm volatile("mbarrier.arrive.shared::cta.b64 _, [%0];" ::"r"(bar) : "memory");
}
__device__ __forceinline__ uint32_t mbar_try(uint32_t bar, uint32_t parity) {
    uint32_t done;
    asm volatile("{\n.reg .pred p;\nmbarrier.try_wait.parity.shared::cta.b64 p, [%1], %2;\nselp.u32 %0, 1, 0, p;\n}\n"
                 : "=r"(done) : "r"(bar), "r"(parity) : "memory");
    return done;
}
__device__ __forceinline__ void mbar_wait(uint32_t bar, uint32_t parity) {
    uint32_t n = 0;
    while (!mbar_try(bar, parity)) {
        if (++n > (1u << 20)) asm volatile("trap;");
    }
}
__device__ __forceinline__ bool elect_one() {
    uint32_t p;
    asm volatile("{\n.reg .pred p;\nelect.sync _|p, 0xffffffff;\nselp.u32 %0, 1, 0, p;\n}\n" : "=r"(p));
    return p != 0;
}
__device__ __forceinline__ void fence_mbar_init() { asm volatile("fence.mbarrier_init.release.cluster;" ::: "memory"); }
__device__ __forceinline__ void fence_proxy_async() { asm volatile("fence.proxy.async.shared::cta;" ::: "memory"); }
__device__ __forceinline__ void tma_load_2d(uint32_t dst, const CUtensorMap* tm, int c0, int c1, uint32_t bar) {
    asm volatile("cp.async.bulk.tensor.2d.shared::cluster.global.mbarrier::complete_tx::bytes [%0], [%1, {%3, %4}], [%2];"
                 ::"r"(dst), "l"(tm), "r"(bar), "r"(c0), "r"(c1) : "memory");
}
__device__ __forceinline__ void tma_store_2d(const CUtensorMap* tm, uint32_t src, int c0, int c1) {
    asm volatile("cp.async.bulk.tensor.2d.global.shared::cta.bulk_group [%0, {%2, %3}], [%1];"
                 ::"l"(tm), "r"(src), "r"(c0), "r"(c1) : "memory");
}
__device__ __forceinline__ void bulk_load(uint32_t dst, const void* src, uint32_t bytes, uint32_t bar) {
    asm volatile("cp.async.bulk.shared::cluster.global.mbarrier::complete_tx::bytes [%0], [%1], %2, [%3];"
                 ::"r"(dst), "l"(src), "r"(bytes), "r"(bar) : "memory");
}
__device__ __forceinline__ void bulk_store(void* dst, uint32_t src, uint32_t bytes) {
    asm volatile("cp.async.bulk.global.shared::cta.bulk_group [%0], [%1], %2;" ::"l"(dst), "r"(src), "r"(bytes) : "memory");
}
__device__ __forceinline__ void l2_prefetch(const void* src, uint32_t bytes) {
    asm volatile("cp.async.bulk.prefetch.L2.global [%0], %1;" ::"l"(src), "r"(bytes) : "memory");
}
__device__ __forceinline__ void tm_prefetch(const CUtensorMap* tm) {
    asm volatile("prefetch.tensormap [%0];" ::"l"(tm) : "memory");
}
__device__ __forceinline__ void pdl_wait() { asm volatile("griddepcontrol.wait;" ::: "memory"); }
__device__ __forceinline__ void pdl_launch() { asm volatile("griddepcontrol.launch_dependents;" ::: "memory"); }
__device__ __forceinline__ void wg_fence() { asm volatile("wgmma.fence.sync.aligned;" ::: "memory"); }
__device__ __forceinline__ void wg_commit() { asm volatile("wgmma.commit_group.sync.aligned;" ::: "memory"); }
template <int N> __device__ __forceinline__ void wg_wait() { asm volatile("wgmma.wait_group.sync.aligned %0;" ::"n"(N) : "memory"); }
template <int N> __device__ __forceinline__ void reg_fence(float (&d)[N]) {
#pragma unroll
    for (int i = 0; i < N; i++) asm volatile("" : "+f"(d[i])::"memory");
}
template <int OFF, int CNT, int N> __device__ __forceinline__ void reg_fence_r(uint32_t (&d)[N]) {
#pragma unroll
    for (int i = OFF; i < OFF + CNT; i++) asm volatile("" : "+r"(d[i])::"memory");
}
template <int N> __device__ __forceinline__ void reg_fence(uint32_t (&d)[N]) {
#pragma unroll
    for (int i = 0; i < N; i++) asm volatile("" : "+r"(d[i])::"memory");
}
__device__ __forceinline__ void bar_sync(int id, int n) { asm volatile("bar.sync %0, %1;" ::"r"(id), "r"(n) : "memory"); }
__device__ __forceinline__ void bar_arrive(int id, int n) { asm volatile("bar.arrive %0, %1;" ::"r"(id), "r"(n) : "memory"); }

struct Desc {
    uint32_t lo, hi;
    __device__ __forceinline__ uint64_t operator+(uint32_t off16) const {
        uint64_t r;
        asm("mov.b64 %0, {%1, %2};" : "=l"(r) : "r"(lo + off16), "r"(hi));
        return r;
    }
};
__device__ __forceinline__ Desc make_desc(uint32_t saddr, uint32_t lbo, uint32_t sbo, uint32_t swz) {
    Desc d;
    d.lo = ((saddr & 0x3FFFF) >> 4) | (((lbo & 0x3FFFF) >> 4) << 16);
    d.hi = ((sbo & 0x3FFFF) >> 4) | (swz << 30);
    return d;
}
__device__ __forceinline__ uint32_t pack_bf16(float lo, float hi) {
    uint32_t r;
    asm("cvt.rn.bf16x2.f32 %0, %1, %2;" : "=r"(r) : "f"(hi), "f"(lo));
    return r;
}
__device__ __forceinline__ float bf_lo(uint32_t v) { return __uint_as_float(v << 16); }
__device__ __forceinline__ float bf_hi(uint32_t v) { return __uint_as_float(v & 0xffff0000u); }
__device__ __forceinline__ float ex2(float x) {
    float r;
    asm("ex2.approx.ftz.f32 %0, %1;" : "=f"(r) : "f"(x));
    return r;
}
__device__ __forceinline__ float tanh_fast(float x) {
    float r;
    asm("tanh.approx.f32 %0, %1;" : "=f"(r) : "f"(x));
    return r;
}
__device__ __forceinline__ uint32_t hfma2_bf16(uint32_t a, uint32_t b, uint32_t c) {
    uint32_t r;
    asm("fma.rn.bf16x2 %0, %1, %2, %3;" : "=r"(r) : "r"(a), "r"(b), "r"(c));
    return r;
}
__device__ __forceinline__ uint32_t sm_id() {
    uint32_t r;
    asm volatile("mov.u32 %0, %%smid;" : "=r"(r));
    return r & 1023;
}
__device__ __forceinline__ uint32_t role_load(int use_map) {
    uint32_t r = blockIdx.x < 128 ? blockIdx.x + 1 : 0;
    if (use_map) asm volatile("ld.relaxed.gpu.global.u32 %0, [%1];" : "=r"(r) : "l"(&g_role[sm_id()]) : "memory");
    return r;
}
__device__ __forceinline__ int role_get(uint32_t r) { return __shfl_sync(0xffffffffu, (int)r - 1, 0); }
__device__ __forceinline__ void check_in(int k) { asm volatile("red.relaxed.gpu.global.add.u32 [%0], 1;" ::"l"(&g_cnt[k]) : "memory"); }
__device__ __forceinline__ void spare_hold(int k) {
    uint32_t v, n = 0;
    do {
        asm volatile("ld.relaxed.gpu.global.u32 %0, [%1];" : "=r"(v) : "l"(&g_cnt[k]) : "memory");
        if (++n > (1u << 22)) asm volatile("trap;");
        __nanosleep(100);
    } while (v < 128);
}
__device__ __forceinline__ int stat_idx(int r0, int c) { return (((r0 >> 4) * 8 + c) * 8 + (r0 & 7)) * 2; }
__device__ __forceinline__ float gelu_h(float hx) {
    float u = hx * fmaf(hx * hx, 8.f * 0.044715f * 0.7978845608028654f, 2.f * 0.7978845608028654f);
    return fmaf(hx, tanh_fast(u), hx);
}

__device__ __forceinline__ void wgmma_ss_n192_t(float (&d)[96], uint64_t da, uint64_t db, int acc) {
    asm volatile("{\n.reg .pred p;\nsetp.ne.b32 p, %98, 0;\n"
        "wgmma.mma_async.sync.aligned.m64n192k16.f32.bf16.bf16 {%0,%1,%2,%3,%4,%5,%6,%7,%8,%9,%10,%11,%12,%13,%14,%15,%16,%17,%18,%19,%20,%21,%22,%23,%24,%25,%26,%27,%28,%29,%30,%31,%32,%33,%34,%35,%36,%37,%38,%39,%40,%41,%42,%43,%44,%45,%46,%47,%48,%49,%50,%51,%52,%53,%54,%55,%56,%57,%58,%59,%60,%61,%62,%63,%64,%65,%66,%67,%68,%69,%70,%71,%72,%73,%74,%75,%76,%77,%78,%79,%80,%81,%82,%83,%84,%85,%86,%87,%88,%89,%90,%91,%92,%93,%94,%95}, %96, %97, p, 1, 1, 0, 1;\n}\n"
        : "+f"(d[0]), "+f"(d[1]), "+f"(d[2]), "+f"(d[3]), "+f"(d[4]), "+f"(d[5]), "+f"(d[6]), "+f"(d[7]), "+f"(d[8]), "+f"(d[9]), "+f"(d[10]), "+f"(d[11]), "+f"(d[12]), "+f"(d[13]), "+f"(d[14]), "+f"(d[15]), "+f"(d[16]), "+f"(d[17]), "+f"(d[18]), "+f"(d[19]), "+f"(d[20]), "+f"(d[21]), "+f"(d[22]), "+f"(d[23]), "+f"(d[24]), "+f"(d[25]), "+f"(d[26]), "+f"(d[27]), "+f"(d[28]), "+f"(d[29]), "+f"(d[30]), "+f"(d[31]), "+f"(d[32]), "+f"(d[33]), "+f"(d[34]), "+f"(d[35]), "+f"(d[36]), "+f"(d[37]), "+f"(d[38]), "+f"(d[39]), "+f"(d[40]), "+f"(d[41]), "+f"(d[42]), "+f"(d[43]), "+f"(d[44]), "+f"(d[45]), "+f"(d[46]), "+f"(d[47]), "+f"(d[48]), "+f"(d[49]), "+f"(d[50]), "+f"(d[51]), "+f"(d[52]), "+f"(d[53]), "+f"(d[54]), "+f"(d[55]), "+f"(d[56]), "+f"(d[57]), "+f"(d[58]), "+f"(d[59]), "+f"(d[60]), "+f"(d[61]), "+f"(d[62]), "+f"(d[63]), "+f"(d[64]), "+f"(d[65]), "+f"(d[66]), "+f"(d[67]), "+f"(d[68]), "+f"(d[69]), "+f"(d[70]), "+f"(d[71]), "+f"(d[72]), "+f"(d[73]), "+f"(d[74]), "+f"(d[75]), "+f"(d[76]), "+f"(d[77]), "+f"(d[78]), "+f"(d[79]), "+f"(d[80]), "+f"(d[81]), "+f"(d[82]), "+f"(d[83]), "+f"(d[84]), "+f"(d[85]), "+f"(d[86]), "+f"(d[87]), "+f"(d[88]), "+f"(d[89]), "+f"(d[90]), "+f"(d[91]), "+f"(d[92]), "+f"(d[93]), "+f"(d[94]), "+f"(d[95])
        : "l"(da), "l"(db), "r"(acc));
}

__device__ __forceinline__ void wgmma_ss_n112_t(float (&d)[56], uint64_t da, uint64_t db, int acc) {
    asm volatile("{\n.reg .pred p;\nsetp.ne.b32 p, %58, 0;\n"
        "wgmma.mma_async.sync.aligned.m64n112k16.f32.bf16.bf16 {%0,%1,%2,%3,%4,%5,%6,%7,%8,%9,%10,%11,%12,%13,%14,%15,%16,%17,%18,%19,%20,%21,%22,%23,%24,%25,%26,%27,%28,%29,%30,%31,%32,%33,%34,%35,%36,%37,%38,%39,%40,%41,%42,%43,%44,%45,%46,%47,%48,%49,%50,%51,%52,%53,%54,%55}, %56, %57, p, 1, 1, 0, 1;\n}\n"
        : "+f"(d[0]), "+f"(d[1]), "+f"(d[2]), "+f"(d[3]), "+f"(d[4]), "+f"(d[5]), "+f"(d[6]), "+f"(d[7]), "+f"(d[8]), "+f"(d[9]), "+f"(d[10]), "+f"(d[11]), "+f"(d[12]), "+f"(d[13]), "+f"(d[14]), "+f"(d[15]), "+f"(d[16]), "+f"(d[17]), "+f"(d[18]), "+f"(d[19]), "+f"(d[20]), "+f"(d[21]), "+f"(d[22]), "+f"(d[23]), "+f"(d[24]), "+f"(d[25]), "+f"(d[26]), "+f"(d[27]), "+f"(d[28]), "+f"(d[29]), "+f"(d[30]), "+f"(d[31]), "+f"(d[32]), "+f"(d[33]), "+f"(d[34]), "+f"(d[35]), "+f"(d[36]), "+f"(d[37]), "+f"(d[38]), "+f"(d[39]), "+f"(d[40]), "+f"(d[41]), "+f"(d[42]), "+f"(d[43]), "+f"(d[44]), "+f"(d[45]), "+f"(d[46]), "+f"(d[47]), "+f"(d[48]), "+f"(d[49]), "+f"(d[50]), "+f"(d[51]), "+f"(d[52]), "+f"(d[53]), "+f"(d[54]), "+f"(d[55])
        : "l"(da), "l"(db), "r"(acc));
}

__device__ __forceinline__ void wgmma_ss_n64_t(float (&d)[32], uint64_t da, uint64_t db, int acc) {
    asm volatile("{\n.reg .pred p;\nsetp.ne.b32 p, %34, 0;\n"
        "wgmma.mma_async.sync.aligned.m64n64k16.f32.bf16.bf16 {%0,%1,%2,%3,%4,%5,%6,%7,%8,%9,%10,%11,%12,%13,%14,%15,%16,%17,%18,%19,%20,%21,%22,%23,%24,%25,%26,%27,%28,%29,%30,%31}, %32, %33, p, 1, 1, 0, 1;\n}\n"
        : "+f"(d[0]), "+f"(d[1]), "+f"(d[2]), "+f"(d[3]), "+f"(d[4]), "+f"(d[5]), "+f"(d[6]), "+f"(d[7]), "+f"(d[8]), "+f"(d[9]), "+f"(d[10]), "+f"(d[11]), "+f"(d[12]), "+f"(d[13]), "+f"(d[14]), "+f"(d[15]), "+f"(d[16]), "+f"(d[17]), "+f"(d[18]), "+f"(d[19]), "+f"(d[20]), "+f"(d[21]), "+f"(d[22]), "+f"(d[23]), "+f"(d[24]), "+f"(d[25]), "+f"(d[26]), "+f"(d[27]), "+f"(d[28]), "+f"(d[29]), "+f"(d[30]), "+f"(d[31])
        : "l"(da), "l"(db), "r"(acc));
}

__device__ __forceinline__ void wgmma_ss_n128_z(float (&d)[64], uint64_t da, uint64_t db) {
    asm volatile("wgmma.mma_async.sync.aligned.m64n128k16.f32.bf16.bf16 {%0,%1,%2,%3,%4,%5,%6,%7,%8,%9,%10,%11,%12,%13,%14,%15,%16,%17,%18,%19,%20,%21,%22,%23,%24,%25,%26,%27,%28,%29,%30,%31,%32,%33,%34,%35,%36,%37,%38,%39,%40,%41,%42,%43,%44,%45,%46,%47,%48,%49,%50,%51,%52,%53,%54,%55,%56,%57,%58,%59,%60,%61,%62,%63}, %64, %65, 0, 1, 1, 0, 0;\n"
        : "+f"(d[0]), "+f"(d[1]), "+f"(d[2]), "+f"(d[3]), "+f"(d[4]), "+f"(d[5]), "+f"(d[6]), "+f"(d[7]), "+f"(d[8]), "+f"(d[9]), "+f"(d[10]), "+f"(d[11]), "+f"(d[12]), "+f"(d[13]), "+f"(d[14]), "+f"(d[15]), "+f"(d[16]), "+f"(d[17]), "+f"(d[18]), "+f"(d[19]), "+f"(d[20]), "+f"(d[21]), "+f"(d[22]), "+f"(d[23]), "+f"(d[24]), "+f"(d[25]), "+f"(d[26]), "+f"(d[27]), "+f"(d[28]), "+f"(d[29]), "+f"(d[30]), "+f"(d[31]), "+f"(d[32]), "+f"(d[33]), "+f"(d[34]), "+f"(d[35]), "+f"(d[36]), "+f"(d[37]), "+f"(d[38]), "+f"(d[39]), "+f"(d[40]), "+f"(d[41]), "+f"(d[42]), "+f"(d[43]), "+f"(d[44]), "+f"(d[45]), "+f"(d[46]), "+f"(d[47]), "+f"(d[48]), "+f"(d[49]), "+f"(d[50]), "+f"(d[51]), "+f"(d[52]), "+f"(d[53]), "+f"(d[54]), "+f"(d[55]), "+f"(d[56]), "+f"(d[57]), "+f"(d[58]), "+f"(d[59]), "+f"(d[60]), "+f"(d[61]), "+f"(d[62]), "+f"(d[63])
        : "l"(da), "l"(db));
}

__device__ __forceinline__ void wgmma_ss_n64_z(float (&d)[32], uint64_t da, uint64_t db) {
    asm volatile("wgmma.mma_async.sync.aligned.m64n64k16.f32.bf16.bf16 {%0,%1,%2,%3,%4,%5,%6,%7,%8,%9,%10,%11,%12,%13,%14,%15,%16,%17,%18,%19,%20,%21,%22,%23,%24,%25,%26,%27,%28,%29,%30,%31}, %32, %33, 0, 1, 1, 0, 0;\n"
        : "+f"(d[0]), "+f"(d[1]), "+f"(d[2]), "+f"(d[3]), "+f"(d[4]), "+f"(d[5]), "+f"(d[6]), "+f"(d[7]), "+f"(d[8]), "+f"(d[9]), "+f"(d[10]), "+f"(d[11]), "+f"(d[12]), "+f"(d[13]), "+f"(d[14]), "+f"(d[15]), "+f"(d[16]), "+f"(d[17]), "+f"(d[18]), "+f"(d[19]), "+f"(d[20]), "+f"(d[21]), "+f"(d[22]), "+f"(d[23]), "+f"(d[24]), "+f"(d[25]), "+f"(d[26]), "+f"(d[27]), "+f"(d[28]), "+f"(d[29]), "+f"(d[30]), "+f"(d[31])
        : "l"(da), "l"(db));
}

__device__ __forceinline__ void wgmma_rs_n24_t(float (&d)[12], uint32_t a0, uint32_t a1, uint32_t a2, uint32_t a3, uint64_t db) {
    asm volatile("wgmma.mma_async.sync.aligned.m64n24k16.f32.bf16.bf16 {%0,%1,%2,%3,%4,%5,%6,%7,%8,%9,%10,%11}, {%12,%13,%14,%15}, %16, 1, 1, 1, 1;\n"
        : "+f"(d[0]), "+f"(d[1]), "+f"(d[2]), "+f"(d[3]), "+f"(d[4]), "+f"(d[5]), "+f"(d[6]), "+f"(d[7]), "+f"(d[8]), "+f"(d[9]), "+f"(d[10]), "+f"(d[11])
        : "r"(a0), "r"(a1), "r"(a2), "r"(a3), "l"(db));
}

constexpr int P1_STAGES = 5;
#define ST_DELAY 800
constexpr int P1_STAGE_BYTES = 16384 + 24576;
constexpr int P1_AUX = P1_STAGES * P1_STAGE_BYTES;
constexpr int P1_SMEM = P1_AUX + 128 + 128 * 8 + 192 * 4;

__device__ __forceinline__ uint32_t enc_f(float v) { return v != v ? 0x80000000u : ~__float_as_uint(v); }
__device__ __forceinline__ float dec_f(uint32_t w) { return __uint_as_float(~w); }
__device__ __forceinline__ uint4 ld_relaxed4(const uint32_t* p) {
    uint4 v;
    asm volatile("ld.relaxed.gpu.global.v4.u32 {%0,%1,%2,%3}, [%4];" : "=r"(v.x), "=r"(v.y), "=r"(v.z), "=r"(v.w) : "l"(p) : "memory");
    return v;
}
__global__ void __launch_bounds__(416, 1)
k_qkv(const __grid_constant__ CUtensorMap tm_x, const __grid_constant__ CUtensorMap tm_w,
      const __nv_bfloat16* __restrict__ x, const __nv_bfloat16* __restrict__ wqkv) {
    extern __shared__ __align__(1024) uint8_t smem[];
    const uint32_t sb = smem_u32(smem);
    const uint32_t bar_full = sb + P1_AUX, bar_empty = bar_full + 8 * P1_STAGES;
    float2* s_row = reinterpret_cast<float2*>(smem + P1_AUX + 128);
    float* s_cs = reinterpret_cast<float*>(smem + P1_AUX + 128 + 1024);
    const int tid = threadIdx.x, warp = __shfl_sync(0xffffffffu, tid >> 5, 0), lane = tid & 31;
    const int bid = blockIdx.x, rb = bid >> 3, c = bid & 7;
    TS0(0, 0);
    if (warp >= 8 && warp < 12) {
        const int w = warp - 8, ch = lane & 7, rs = lane >> 3;
        uint4 xv[8], wv[8];
        bar_arrive(0, 416);
        __nanosleep(ST_DELAY);
        const uint4* xp = reinterpret_cast<const uint4*>(x + (size_t)(rb * 128 + w * 32 + rs) * DM + c * 64) + ch;
#pragma unroll
        for (int i = 0; i < 8; i++) xv[i] = __ldg(xp + i * 4 * (DM / 8));
        if (w < 3) {
            const uint4* wp = reinterpret_cast<const uint4*>(wqkv + (size_t)(rb * 32 + rs) * (3 * DM) + w * DM + c * 64) + ch;
#pragma unroll
            for (int i = 0; i < 8; i++) wv[i] = __ldg(wp + i * 4 * (3 * DM / 8));
        }
#pragma unroll
        for (int i = 0; i < 8; i++) {
            const uint32_t u[4] = {xv[i].x, xv[i].y, xv[i].z, xv[i].w};
            float sm = 0.f, sq = 0.f;
#pragma unroll
            for (int e = 0; e < 4; e++) {
                const float a = bf_lo(u[e]), b = bf_hi(u[e]);
                sm += a + b; sq = fmaf(a, a, fmaf(b, b, sq));
            }
#pragma unroll
            for (int o = 1; o < 8; o <<= 1) { sm += __shfl_xor_sync(0xffffffffu, sm, o); sq += __shfl_xor_sync(0xffffffffu, sq, o); }
            if (ch == 0)
                asm volatile("st.relaxed.gpu.global.v2.u32 [%0], {%1, %2};" ::"l"(&g_xst[bid * 256 + (w * 32 + i * 4 + rs) * 2]), "r"(enc_f(sm)), "r"(enc_f(sq)) : "memory");
        }
        if (w < 3) {
            float cs[8];
#pragma unroll
            for (int i = 0; i < 8; i++) cs[i] = 0.f;
#pragma unroll
            for (int i = 0; i < 8; i++) {
                cs[0] += bf_lo(wv[i].x); cs[1] += bf_hi(wv[i].x);
                cs[2] += bf_lo(wv[i].y); cs[3] += bf_hi(wv[i].y);
                cs[4] += bf_lo(wv[i].z); cs[5] += bf_hi(wv[i].z);
                cs[6] += bf_lo(wv[i].w); cs[7] += bf_hi(wv[i].w);
            }
#pragma unroll
            for (int i = 0; i < 8; i++) {
                cs[i] += __shfl_xor_sync(0xffffffffu, cs[i], 8);
                cs[i] += __shfl_xor_sync(0xffffffffu, cs[i], 16);
            }
            if (rs < 2) {
                const float a0 = rs ? cs[4] : cs[0], a1 = rs ? cs[5] : cs[1], a2 = rs ? cs[6] : cs[2], a3 = rs ? cs[7] : cs[3];
                asm volatile("st.relaxed.gpu.global.v4.u32 [%0], {%1, %2, %3, %4};" ::"l"(&g_wcs[(c * 16 + rb) * 192 + w * 64 + ch * 8 + rs * 4]),
                             "r"(enc_f(a0)), "r"(enc_f(a1)), "r"(enc_f(a2)), "r"(enc_f(a3)) : "memory");
            }
        }
        if (tid == 256) TSP(0, 6);
        const int hl = lane >> 4, l16 = lane & 15;
        const uint32_t* pr = &g_xst[(rb * 8 + hl * 4) * 256 + (w * 32 + l16 * 2) * 2];
        const uint32_t* pc = &g_wcs[(c * 16 + hl * 8) * 192 + (w * 12 + (l16 < 12 ? l16 : 0)) * 4];
        __nanosleep(300);
        uint32_t n = 0;
        while (true) {
            uint32_t ok = 1;
#pragma unroll
            for (int i = 0; i < 4; i++) { xv[i] = ld_relaxed4(pr + i * 256); }
#pragma unroll
            for (int i = 0; i < 8; i++) { wv[i] = ld_relaxed4(pc + i * 192); }
#pragma unroll
            for (int i = 0; i < 4; i++) ok &= (xv[i].x != 0) & (xv[i].y != 0) & (xv[i].z != 0) & (xv[i].w != 0);
#pragma unroll
            for (int i = 0; i < 8; i++) ok &= (wv[i].x != 0) & (wv[i].y != 0) & (wv[i].z != 0) & (wv[i].w != 0);
            if (__all_sync(0xffffffffu, ok)) break;
            if (++n > (1u << 20)) asm volatile("trap;");
            __nanosleep(100);
        }
        float r[4] = {0.f, 0.f, 0.f, 0.f}, q[4] = {0.f, 0.f, 0.f, 0.f};
#pragma unroll
        for (int i = 0; i < 4; i++) { r[0] += dec_f(xv[i].x); r[1] += dec_f(xv[i].y); r[2] += dec_f(xv[i].z); r[3] += dec_f(xv[i].w); }
#pragma unroll
        for (int i = 0; i < 8; i++) { q[0] += dec_f(wv[i].x); q[1] += dec_f(wv[i].y); q[2] += dec_f(wv[i].z); q[3] += dec_f(wv[i].w); }
#pragma unroll
        for (int i = 0; i < 4; i++) { r[i] += __shfl_xor_sync(0xffffffffu, r[i], 16); q[i] += __shfl_xor_sync(0xffffffffu, q[i], 16); }
        {
            const float sm = hl ? r[2] : r[0], sq = hl ? r[3] : r[1];
            const float mean = sm * (1.f / DM), var = fmaxf(sq * (1.f / DM) - mean * mean, 0.f);
            s_row[w * 32 + l16 * 2 + hl] = make_float2(mean, rsqrtf(var + LN_EPS));
        }
        if (lane < 12) *reinterpret_cast<float4*>(&s_cs[(w * 12 + lane) * 4]) = make_float4(q[0], q[1], q[2], q[3]);
        if (tid == 256) TSP(0, 7);
        bar_arrive(1, 384);
        return;
    }
    if (tid == 384) {
        if (sb & 1023) asm volatile("trap;");
        for (int s = 0; s < P1_STAGES; s++) { mbar_init(bar_full + 8 * s, 1); mbar_init(bar_empty + 8 * s, 8); }
        fence_mbar_init();
        for (int kb = 0; kb < P1_STAGES; kb++) {
            uint32_t st = sb + kb * P1_STAGE_BYTES, fb = bar_full + 8 * kb;
            mbar_expect_tx(fb, P1_STAGE_BYTES);
            tma_load_2d(st, &tm_x, kb * 64, rb * 128, fb);
            tma_load_2d(st + 16384, &tm_w, c * 64, kb * 64, fb);
            tma_load_2d(st + 16384 + 8192, &tm_w, 512 + c * 64, kb * 64, fb);
            tma_load_2d(st + 16384 + 16384, &tm_w, 1024 + c * 64, kb * 64, fb);
        }
    }
    if (tid == 0) g_role[sm_id()] = bid + 1;
    if (bid == 0 && tid < 8) g_cnt[tid] = 0;
    bar_sync(0, 416);
    pdl_launch();
    if (warp == 12) {
        if (elect_one()) {
            for (int kb = P1_STAGES; kb < 8; kb++) {
                int s = kb % P1_STAGES;
                mbar_wait(bar_empty + 8 * s, 0);
                uint32_t st = sb + s * P1_STAGE_BYTES, fb = bar_full + 8 * s;
                mbar_expect_tx(fb, P1_STAGE_BYTES);
                tma_load_2d(st, &tm_x, kb * 64, rb * 128, fb);
                tma_load_2d(st + 16384, &tm_w, c * 64, kb * 64, fb);
                tma_load_2d(st + 16384 + 8192, &tm_w, 512 + c * 64, kb * 64, fb);
                tma_load_2d(st + 16384 + 16384, &tm_w, 1024 + c * 64, kb * 64, fb);
            }
        }
    } else {
        const int wg = warp >> 2;
        float acc[96];
        for (int kb = 0; kb < 8; kb++) {
            int s = kb % P1_STAGES;
            mbar_wait(bar_full + 8 * s, (kb / P1_STAGES) & 1);
            uint32_t st = sb + s * P1_STAGE_BYTES;
            if (kb == 0) TS0(0, 2);
            const Desc da = make_desc(st + wg * 8192, 16, 1024, 1);
            const Desc db = make_desc(st + 16384, 8192, 1024, 1);
            wg_fence();
#pragma unroll
            for (int k = 0; k < 4; k++) wgmma_ss_n192_t(acc, da + k * 2, db + k * 128, kb | k);
            wg_commit();
            if (kb > 0) {
                wg_wait<1>();
                if (lane == 0) mbar_arrive(bar_empty + 8 * ((kb - 1) % P1_STAGES));
            }
        }
        wg_wait<0>();
        reg_fence(acc);
        TS0(0, 3);
        bar_sync(1, 384);
        TS0(0, 4);
        const int q4 = lane & 3;
        const int r0 = warp * 16 + (lane >> 2);
        const float2 st0 = s_row[r0], st1 = s_row[r0 + 8];
        const int rg = rb * 16 + warp * 2;
        constexpr float QS = 0.25f * 1.4426950408889634f;
        float vmax = 0.f;
        float kn[8];
#pragma unroll
        for (int j = 0; j < 24; j++) {
            const int sec = j >> 3, jj = j & 7, head = 4 * c + (jj >> 1), half = jj & 1;
            float2 csv = *reinterpret_cast<const float2*>(&s_cs[j * 8 + q4 * 2]);
            float sc0 = sec == 0 ? st0.y * QS : st0.y, sc1 = sec == 0 ? st1.y * QS : st1.y;
            float v0 = sc0 * fmaf(-st0.x, csv.x, acc[4 * j + 0]);
            float v1 = sc0 * fmaf(-st0.x, csv.y, acc[4 * j + 1]);
            float v2 = sc1 * fmaf(-st1.x, csv.x, acc[4 * j + 2]);
            float v3 = sc1 * fmaf(-st1.x, csv.y, acc[4 * j + 3]);
            uint32_t p0 = pack_bf16(v0, v1), p1 = pack_bf16(v2, v3);
            if (sec < 2) {
                uint32_t* dst = (sec == 0 ? g_q : g_k) + ((head * 256 + rg) * 2 + half) * 32 + lane;
                dst[0] = p0;
                dst[64] = p1;
            } else {
                uint32_t* dst = g_v + ((head * 2 + half) * 256 + rg) * 32 + lane;
                dst[0] = p0;
                dst[32] = p1;
            }
            if (sec < 2) {
                acc[4 * j + 0] = v0 * v0 + v1 * v1;
                acc[4 * j + 2] = v2 * v2 + v3 * v3;
            }
            if (sec == 2) {
                uint32_t m = max(max(__float_as_uint(fabsf(v0)), __float_as_uint(fabsf(v1))),
                                 max(__float_as_uint(fabsf(v2)), __float_as_uint(fabsf(v3))));
                vmax = __uint_as_float(max(__float_as_uint(vmax), m));
            }
        }
#pragma unroll
        for (int hh = 0; hh < 8; hh++) {
            float a = acc[4 * (2 * hh) + 0] + acc[4 * (1 + 2 * hh) + 0];
            float b = acc[4 * (2 * hh) + 2] + acc[4 * (1 + 2 * hh) + 2];
            a += __shfl_xor_sync(0xffffffffu, a, 1); b += __shfl_xor_sync(0xffffffffu, b, 1);
            a += __shfl_xor_sync(0xffffffffu, a, 2); b += __shfl_xor_sync(0xffffffffu, b, 2);
            uint32_t m = max(__float_as_uint(fabsf(a)), __float_as_uint(fabsf(b)));
            m = __reduce_max_sync(0xffffffffu, m);
            kn[hh] = __uint_as_float(m);
        }
        uint32_t vm = __reduce_max_sync(0xffffffffu, __float_as_uint(vmax));
        if (lane < 4) {
            float kk = lane == 0 ? kn[4] : lane == 1 ? kn[5] : lane == 2 ? kn[6] : kn[7];
            float qq = lane == 0 ? kn[0] : lane == 1 ? kn[1] : lane == 2 ? kn[2] : kn[3];
            g_kv[(4 * c + lane) * 128 + rb * 8 + warp] = make_float2(kk, __uint_as_float(vm));
            g_qn[(4 * c + lane) * 128 + rb * 8 + warp] = qq;
        }
        TS0(0, 5);
    }
}

constexpr int P2_K = 0, P2_V = 65536, P2_ONES = 131072, P2_Q = 163840, P2_AUX = 180224;
constexpr int P2_SMEM = P2_AUX + 1024;
constexpr int P2_NCH = 8;
#define ATT_MASK 0x92499249u

__device__ __forceinline__ uint32_t exp2_pair_mufu(float x0, float x1) { return pack_bf16(ex2(x0), ex2(x1)); }
__device__ __forceinline__ uint32_t exp2_pair_fma(float x0, float x1, uint32_t cm, uint32_t ch) {
    constexpr float MAGIC = 8388608.f + 127.f * 32768.f + 128.f - 19212.f;
    float t0 = fmaf(x0, 32768.f, MAGIC), t1 = fmaf(x1, 32768.f, MAGIC);
    uint32_t u = __byte_perm(__float_as_uint(t0), __float_as_uint(t1), 0x6521);
    uint32_t m, e = u & 0xFF80FF80u;
    asm("lop3.b32 %0, %1, %2, %3, 0xEA;" : "=r"(m) : "r"(u), "r"(cm), "r"(ch));
    return hfma2_bf16(u, m, e);
}
template <int OFF> __device__ __forceinline__ void desc_add(uint64_t& d) {
    asm volatile("{\n.reg .b32 l, h;\nmov.b64 {l, h}, %0;\nadd.u32 l, l, %1;\nmov.b64 %0, {l, h};\n}\n" : "+l"(d) : "n"(OFF));
}
template <int OFF, int CNT> __device__ __forceinline__ void exp_part(const float (&s)[32], uint32_t (&p)[16], uint32_t mask, uint32_t cm, uint32_t ch) {
#pragma unroll
    for (int i = OFF; i < OFF + CNT; i++) {
        if ((mask >> i) & 1) p[i] = exp2_pair_mufu(s[2 * i], s[2 * i + 1]);
        else p[i] = exp2_pair_fma(s[2 * i], s[2 * i + 1], cm, ch);
    }
}
__device__ __forceinline__ void attn_store(const float (&o)[12], int row, int head, int lane) {
    const float i0 = 1.f / o[8], i1 = 1.f / o[10];
    uint32_t* dst = g_o + (((row >> 7) * 64 + head * 2) * 16 + ((row & 127) >> 3)) * 32 + lane;
    dst[0] = pack_bf16(o[0] * i0, o[1] * i0);
    dst[32] = pack_bf16(o[2] * i1, o[3] * i1);
    dst[512] = pack_bf16(o[4] * i0, o[5] * i0);
    dst[544] = pack_bf16(o[6] * i1, o[7] * i1);
}

template <uint32_t MASK> __device__ __forceinline__ void attn_fast(const Desc dk, const Desc dv, const Desc dq, uint32_t bar_kv, int row0, int head, int lane, int wg, int bid) {
    const uint32_t cm = 0x007F007Fu, ch = 0x3F003F00u;
    uint32_t offs[8];
#pragma unroll
    for (int t = 0; t < 8; t++) offs[t] = __shfl_sync(0xffffffffu, lane * 16, t);
    const uint32_t ko1 = __shfl_sync(0xffffffffu, lane * 16, 8), ko2 = __shfl_sync(0xffffffffu, lane * 16, 16);
    const uint32_t qo1 = __shfl_sync(0xffffffffu, lane, 0);
    mbar_wait(bar_kv, 0);
    TS0(1, 6);
#pragma unroll 1
    for (int ti = 0; ti < 2; ti++) {
        float o[12], s[32];
        uint32_t p[16];
        uint64_t dvv[8], dkk[2], dqq[2];
#pragma unroll
        for (int t = 0; t < 8; t++) dvv[t] = dv + offs[t];
        dkk[0] = dk + ko1; dkk[1] = dk + ko2;
        dqq[0] = dq + (uint32_t)ti * 128; dqq[1] = dq + ((uint32_t)ti * 128 + qo1);
#pragma unroll
        for (int i = 0; i < 12; i++) o[i] = 0.f;
        reg_fence(o);
        wg_fence();
        wgmma_ss_n64_z(s, dqq[0], dk + 0u);
        wg_commit();
#pragma unroll 1
        for (int blk = 0; blk < 8; blk++) {
            mbar_wait(bar_kv + 8 * blk, 0);
#pragma unroll 1
            for (int h2 = 0; h2 < 2; h2++) {
#pragma unroll
                for (int h = 0; h < 2; h++) {
                    wg_wait<0>();
                    reg_fence(s);
                    reg_fence(o);
                    exp_part<0, 16>(s, p, MASK >> (16 * h), cm, ch);
                    reg_fence(p);
                    wg_fence();
                    wgmma_ss_n64_z(s, dqq[h], dkk[h]);
                    desc_add<256>(dkk[h]);
#pragma unroll
                    for (int t = 0; t < 4; t++) {
                        wgmma_rs_n24_t(o, p[4 * t], p[4 * t + 1], p[4 * t + 2], p[4 * t + 3], dvv[4 * h + t]);
                        desc_add<128>(dvv[4 * h + t]);
                    }
                    wg_commit();
                }
            }
        }
        wg_wait<0>();
        reg_fence(s);
        reg_fence(o);
        attn_store(o, row0 + ti * 64, head, lane);
        TS0(1, 3 + ti);
        if (wg) TS(1, 8 + ti * 4 + wg);
    }
}

__global__ void __launch_bounds__(544, 1)
k_attn(const __nv_bfloat16* __restrict__ w_in, const __nv_bfloat16* __restrict__ wo,
       const __nv_bfloat16* __restrict__ w_sp, const __nv_bfloat16* __restrict__ w_out, int use_map) {
    extern __shared__ __align__(1024) uint8_t smem[];
    const uint32_t sb = smem_u32(smem);
    const int tid = threadIdx.x, warp = __shfl_sync(0xffffffffu, tid >> 5, 0), lane = tid & 31;
    const uint32_t rraw = role_load(use_map);
    const uint32_t bar_kv = sb + P2_AUX;
    if (tid == 0) {
        if (sb & 1023) asm volatile("trap;");
        for (int i = 0; i <= P2_NCH; i++) mbar_init(bar_kv + 8 * i, 1);
        fence_mbar_init();
    }
    {
        uint4 ones = make_uint4(0x3F803F80u, 0x3F803F80u, 0x3F803F80u, 0x3F803F80u);
        uint4* dst = reinterpret_cast<uint4*>(smem + P2_ONES);
#pragma unroll
        for (int i = 0; i < 4; i++) if (tid < 512) dst[tid + i * 512] = ones;
        fence_proxy_async();
    }
    __syncthreads();
    pdl_launch();
    const int bid = role_get(rraw);
    if (bid < 0) {
        pdl_wait();
        float* red = reinterpret_cast<float*>(smem);
        if (tid == 0) reinterpret_cast<volatile uint32_t*>(smem)[4000] = atomicAdd(&g_cnt[4], 1u);
        __syncthreads();
        const int sp = reinterpret_cast<volatile uint32_t*>(smem)[4000];
        if (tid == 512) spare_hold(0);
        if (sp >= 4) return;
        if (tid < 448) {
            const int cc = tid % 56, sl = tid / 56;
            const uint4* src = reinterpret_cast<const uint4*>(w_in + (size_t)sl * 64 * FF + sp * 448 + cc * 8);
            float cs[8];
#pragma unroll
            for (int i = 0; i < 8; i++) cs[i] = 0.f;
#pragma unroll 16
            for (int r = 0; r < 64; r++) {
                uint4 v = __ldg(src + (size_t)r * (FF / 8));
                cs[0] += bf_lo(v.x); cs[1] += bf_hi(v.x);
                cs[2] += bf_lo(v.y); cs[3] += bf_hi(v.y);
                cs[4] += bf_lo(v.z); cs[5] += bf_hi(v.z);
                cs[6] += bf_lo(v.w); cs[7] += bf_hi(v.w);
            }
#pragma unroll
            for (int i = 0; i < 8; i++) red[sl * 448 + cc * 8 + i] = cs[i];
        }
        __syncthreads();
        if (tid < 448) {
            float s = 0.f;
#pragma unroll
            for (int i = 0; i < 8; i++) s += red[i * 448 + tid];
            g_csin[(sp ^ 2) * 448 + tid] = s;
        }
        return;
    }
    const int head = bid >> 2, qq = bid & 3;
    TS0(1, 0);
    pdl_wait();
    TS0(1, 1);
    if (warp == 16) {
        if (elect_one()) {
            const uint8_t* gk = reinterpret_cast<const uint8_t*>(g_k) + (size_t)head * 65536;
            const uint8_t* gv = reinterpret_cast<const uint8_t*>(g_v) + (size_t)head * 65536;
            for (int i = 0; i < P2_NCH; i++) {
                uint32_t b = bar_kv + 8 * i;
                const uint32_t ko = i == 0 ? 0 : i * 8192 + 2048, kn = i == 0 ? 10240 : i == 7 ? 6144 : 8192;
                mbar_expect_tx(b, (i == 0 ? 16384 : 0) + 8192 + kn);
                if (i == 0) bulk_load(sb + P2_Q, reinterpret_cast<const uint8_t*>(g_q) + (size_t)head * 65536 + qq * 16384, 16384, b);
                bulk_load(sb + P2_K + ko, gk + ko, kn, b);
                bulk_load(sb + P2_V + i * 4096, gv + i * 4096, 4096, b);
                bulk_load(sb + P2_V + 32768 + i * 4096, gv + 32768 + i * 4096, 4096, b);
            }
            check_in(0);
            TSP(1, 5);
        }
        {
            const uint4 z4 = make_uint4(0, 0, 0, 0);
            reinterpret_cast<uint4*>(g_xst)[bid * 64 + lane] = z4;
            reinterpret_cast<uint4*>(g_xst)[bid * 64 + 32 + lane] = z4;
            reinterpret_cast<uint4*>(g_wcs)[bid * 48 + lane] = z4;
            if (lane < 16) reinterpret_cast<uint4*>(g_wcs)[bid * 48 + 32 + lane] = z4;
        }
        if (lane == 0) mbar_wait(bar_kv + 8 * (P2_NCH - 1), 0);
        __syncwarp();
        const int img = bid >> 3, kb = bid & 7;
        const uint4* src = reinterpret_cast<const uint4*>(w_in + (size_t)(kb * 64 + (lane & 7)) * FF + (img ^ 8) * 112) + (lane >> 3);
        uint4* dst = g_win + bid * 896 + lane;
#pragma unroll 1
        for (int h = 0; h < 2; h++) {
            uint4 v[16];
#pragma unroll
            for (int i = 0; i < 16; i++) if ((i & 3) < 3 || lane < 16) v[i] = __ldg(src + (i >> 2) * FF + (i & 3) * 4);
#pragma unroll
            for (int i = 0; i < 16; i++) if ((i & 3) < 3 || lane < 16) dst[(i >> 2) * 112 + (i & 3) * 32] = v[i];
            src += 4 * FF; dst += 4 * 112;
        }
        __syncwarp();
        if (elect_one()) {
            const size_t b = bid;
            l2_prefetch(reinterpret_cast<const uint8_t*>(wo) + b * 4096, 4096);
            l2_prefetch(reinterpret_cast<const uint8_t*>(w_sp) + b * 65536, 32768);
            l2_prefetch(reinterpret_cast<const uint8_t*>(w_sp) + b * 65536 + 32768, 32768);
            l2_prefetch(reinterpret_cast<const uint8_t*>(w_out) + b * 7168, 7168);
            TSP(1, 7);
        }
        return;
    }
    const int wg = warp >> 2, wq = warp & 3;
    bool fast;
    {
        const float4* pk = reinterpret_cast<const float4*>(g_kv + head * 128 + lane * 4);
        const float4 a = pk[0], b = pk[1];
        const float qv = g_qn[head * 128 + qq * 32 + wg * 8 + (lane & 7)];
        uint32_t kmax = max(max(__float_as_uint(a.x), __float_as_uint(a.z)), max(__float_as_uint(b.x), __float_as_uint(b.z)));
        uint32_t vmax = max(max(__float_as_uint(a.y), __float_as_uint(a.w)), max(__float_as_uint(b.y), __float_as_uint(b.w)));
        kmax = __reduce_max_sync(0xffffffffu, kmax);
        vmax = __reduce_max_sync(0xffffffffu, vmax);
        const uint32_t qmax = __reduce_max_sync(0xffffffffu, __float_as_uint(qv));
        fast = (__uint_as_float(qmax) * __uint_as_float(kmax) <= 4096.f) && (__uint_as_float(vmax) <= 1.0995116e12f);
    }
    TS0(1, 2);
    const Desc dk = make_desc(sb + P2_K, 128, 256, 0);
    const Desc dv = make_desc(sb + P2_V, 128, 32768, 0);
    const Desc dq = make_desc(sb + P2_Q + wg * 4096, 128, 256, 0);
    const int row0 = qq * 512 + wg * 128 + wq * 16;
    if (fast) {
        attn_fast<ATT_MASK>(dk, dv, dq, bar_kv, row0, head, lane, wg, bid);
    } else {
#pragma unroll 1
        for (int ti = 0; ti < 2; ti++) {
            float o[12];
#pragma unroll
            for (int i = 0; i < 12; i++) o[i] = 0.f;
            uint32_t p[16];
            float s[32];
            float m0 = -INFINITY, m1 = -INFINITY;
#pragma unroll 1
            for (int j = 0; j < 32; j++) {
                mbar_wait(bar_kv + 8 * (j >> 2), 0);
                wg_fence();
                wgmma_ss_n64_z(s, dq + (uint32_t)ti * 128, dk + (uint32_t)j * 128);
                wg_commit();
                wg_wait<0>();
                reg_fence(s);
                float x0 = m0, x1 = m1;
#pragma unroll
                for (int i = 0; i < 8; i++) {
                    x0 = fmaxf(x0, fmaxf(s[4 * i], s[4 * i + 1]));
                    x1 = fmaxf(x1, fmaxf(s[4 * i + 2], s[4 * i + 3]));
                }
                x0 = fmaxf(x0, __shfl_xor_sync(0xffffffffu, x0, 1)); x1 = fmaxf(x1, __shfl_xor_sync(0xffffffffu, x1, 1));
                x0 = fmaxf(x0, __shfl_xor_sync(0xffffffffu, x0, 2)); x1 = fmaxf(x1, __shfl_xor_sync(0xffffffffu, x1, 2));
                float a0 = ex2(m0 - x0), a1 = ex2(m1 - x1);
                m0 = x0; m1 = x1;
#pragma unroll
                for (int i = 0; i < 3; i++) { o[4 * i] *= a0; o[4 * i + 1] *= a0; o[4 * i + 2] *= a1; o[4 * i + 3] *= a1; }
#pragma unroll
                for (int i = 0; i < 8; i++) {
                    p[2 * i] = pack_bf16(ex2(s[4 * i] - m0), ex2(s[4 * i + 1] - m0));
                    p[2 * i + 1] = pack_bf16(ex2(s[4 * i + 2] - m1), ex2(s[4 * i + 3] - m1));
                }
                reg_fence(p);
                reg_fence(o);
                wg_fence();
#pragma unroll
                for (int t = 0; t < 4; t++)
                    wgmma_rs_n24_t(o, p[4 * t], p[4 * t + 1], p[4 * t + 2], p[4 * t + 3], dv + (uint32_t)(j * 4 + t) * 16);
                wg_commit();
                wg_wait<0>();
                reg_fence(o);
            }
            attn_store(o, row0 + ti * 64, head, lane);
        }
    }
}

constexpr int P3_A = 0, P3_B = 131072, P3_AUX = 196608;
constexpr int P3_SMEM = P3_AUX + 128;
#define P3_FA 4
#define P3_FB 2
__global__ void __launch_bounds__(320, 1)
k_oproj(const __grid_constant__ CUtensorMap tm_wo, const __nv_bfloat16* __restrict__ x, int use_map) {
    extern __shared__ __align__(1024) uint8_t smem[];
    const uint32_t sb = smem_u32(smem);
    const uint32_t bar_a = sb + P3_AUX, bar_b = bar_a + 64;
    const int tid = threadIdx.x, warp = __shfl_sync(0xffffffffu, tid >> 5, 0), lane = tid & 31;
    const uint32_t rraw = role_load(use_map);
    if (tid == 288) tm_prefetch(&tm_wo);
    if (tid == 0) {
        if (sb & 1023) asm volatile("trap;");
        for (int i = 0; i < 8; i++) mbar_init(bar_a + 8 * i, 1);
        for (int i = 0; i < 8; i++) mbar_init(bar_b + 8 * i, 1);
        fence_mbar_init();
    }
    __syncthreads();
    const int bid = role_get(rraw), rb = bid >> 3, c = bid & 7;
    if (bid < 0) {
        if (tid == 0) { pdl_wait(); pdl_launch(); spare_hold(1); }
        return;
    }
    TS0(2, 0);
    if (warp == 8) {
        if (elect_one()) {
            pdl_wait();
            TSP(2, 1);
            const uint8_t* src = reinterpret_cast<const uint8_t*>(g_o) + (size_t)rb * 131072;
            for (int i = 0; i < 8; i++) {
                if (i == P3_FA) {
                    pdl_launch();
                    check_in(1);
                }
                if (i >= P3_FA) mbar_wait(bar_a + 8 * (i - P3_FA), 0);
                mbar_expect_tx(bar_a + 8 * i, 16384);
                bulk_load(sb + P3_A + i * 16384, src + i * 16384, 16384, bar_a + 8 * i);
            }
        }
    } else if (warp == 9) {
        if (elect_one()) {
            for (int i = 0; i < 8; i++) {
                if (i >= P3_FB) mbar_wait(bar_b + 8 * (i - P3_FB), 0);
                mbar_expect_tx(bar_b + 8 * i, 8192);
                tma_load_2d(sb + P3_B + i * 8192, &tm_wo, c * 64, i * 64, bar_b + 8 * i);
            }
        }
    } else {
        const int wg = warp >> 2, q4 = lane & 3;
        const int r0 = rb * 128 + warp * 16 + (lane >> 2);
        uint32_t xr[16];
        const uint32_t* xp = reinterpret_cast<const uint32_t*>(x + (size_t)r0 * DM + c * 64 + q4 * 2);
#pragma unroll
        for (int j = 0; j < 8; j++) { xr[2 * j] = __ldg(xp + j * 4); xr[2 * j + 1] = __ldg(xp + 8 * (DM / 2) + j * 4); }
        float acc[32];
        const Desc da = make_desc(sb + P3_A + wg * 1024, 2048, 128, 0);
        const Desc db = make_desc(sb + P3_B, 8192, 1024, 1);
        for (int kb = 0; kb < 8; kb++) {
            mbar_wait(bar_b + 8 * kb, 0);
            mbar_wait(bar_a + 8 * kb, 0);
            if (kb == 0) TS0(2, 2);
            wg_fence();
#pragma unroll
            for (int k = 0; k < 4; k++) wgmma_ss_n64_t(acc, da + (kb * 4 + k) * 256, db + (kb * 4 + k) * 128, kb | k);
            wg_commit();
        }
        wg_wait<0>();
        reg_fence(acc);
        TS0(2, 3);
        pdl_wait();
        float s0 = 0.f, q0 = 0.f, s1 = 0.f, q1 = 0.f;
        uint32_t* dst = g_h + ((rb * 64 + c * 8) * 16 + warp * 2) * 32 + lane;
#pragma unroll
        for (int j = 0; j < 8; j++) {
            uint32_t p0 = pack_bf16(acc[4 * j] + bf_lo(xr[2 * j]), acc[4 * j + 1] + bf_hi(xr[2 * j]));
            uint32_t p1 = pack_bf16(acc[4 * j + 2] + bf_lo(xr[2 * j + 1]), acc[4 * j + 3] + bf_hi(xr[2 * j + 1]));
            dst[j * 512] = p0;
            dst[j * 512 + 32] = p1;
            float a = bf_lo(p0), b = bf_hi(p0), e = bf_lo(p1), f = bf_hi(p1);
            s0 += a + b; q0 = fmaf(a, a, fmaf(b, b, q0));
            s1 += e + f; q1 = fmaf(e, e, fmaf(f, f, q1));
        }
        s0 += __shfl_xor_sync(0xffffffffu, s0, 1); q0 += __shfl_xor_sync(0xffffffffu, q0, 1);
        s1 += __shfl_xor_sync(0xffffffffu, s1, 1); q1 += __shfl_xor_sync(0xffffffffu, q1, 1);
        s0 += __shfl_xor_sync(0xffffffffu, s0, 2); q0 += __shfl_xor_sync(0xffffffffu, q0, 2);
        s1 += __shfl_xor_sync(0xffffffffu, s1, 2); q1 += __shfl_xor_sync(0xffffffffu, q1, 2);
        if (q4 == 0) {
            *reinterpret_cast<float4*>(&g_hstat[stat_idx(r0, c)]) = make_float4(s0, q0, s1, q1);
        } else if (q4 == 1) {
            *reinterpret_cast<float4*>(&g_zstat[stat_idx(r0, c)]) = make_float4(0.f, -1.f, 0.f, -1.f);
        } else if (lane == 2) {
            g_flag[c * 128 + rb * 8 + warp] = 0;
        }
        TS0(2, 4);
    }
}

constexpr int M_WS = 7;
constexpr int M_X = 0, M_W = 131072, M_AUX = M_W + M_WS * 14336;
constexpr int M_SMEM = M_AUX + 256;
#ifndef M_FA
#define M_FA 3
#endif
#ifndef M_FB
#define M_FB 3
#endif
__device__ __forceinline__ float quad_sum(float v) {
    v += __shfl_xor_sync(0xffffffffu, v, 1);
    return v + __shfl_xor_sync(0xffffffffu, v, 2);
}
struct MixPre { float mean0, rstd0, mean1, rstd1; };
template <int PART> __device__ __forceinline__ MixPre mix_gemm1(float (&acc)[56], float (&cv)[28], uint32_t sb, int r0, int c, int wm, int lane, int bid) {
    const uint32_t bar_xf = sb + M_AUX, bar_xe = bar_xf + 64, bar_wf = bar_xe + 64, bar_we = bar_wf + 8 * M_WS;
    const int q4 = lane & 3;
    pdl_wait();
    TS0(3, 1);
    MixPre p;
    {
        const float4 a = *reinterpret_cast<const float4*>(&g_hstat[stat_idx(r0, q4 * 2)]);
        const float4 b = *reinterpret_cast<const float4*>(&g_hstat[stat_idx(r0, q4 * 2 + 1)]);
        const float s0 = quad_sum(a.x + b.x), q0 = quad_sum(a.y + b.y), s1 = quad_sum(a.z + b.z), q1 = quad_sum(a.w + b.w);
        p.mean0 = s0 * (1.f / DM); p.mean1 = s1 * (1.f / DM);
        p.rstd0 = 0.5f * rsqrtf(fmaxf(q0 * (1.f / DM) - p.mean0 * p.mean0, 0.f) + LN_EPS);
        p.rstd1 = 0.5f * rsqrtf(fmaxf(q1 * (1.f / DM) - p.mean1 * p.mean1, 0.f) + LN_EPS);
    }
    {
        const float* cs = g_csin + PART * FH + c * 112 + q4 * 2;
#pragma unroll
        for (int j = 0; j < 14; j++) { const float2 t = *reinterpret_cast<const float2*>(cs + j * 8); cv[2 * j] = t.x; cv[2 * j + 1] = t.y; }
    }
    const Desc da = make_desc(sb + M_X + wm * 1024, 2048, 128, 0);
    if (PART == 1) bar_sync(1, 512);
    uint32_t s = (PART * 8) % M_WS, pw = ((PART * 8) / M_WS) & 1, sp = 0;
#pragma unroll 1
    for (int kb = 0; kb < 8; kb++) {
        if (PART == 0) mbar_wait(bar_xf + 8 * kb, 0);
        mbar_wait(bar_wf + 8 * s, pw);
        if (kb == 0) TS0(3, 2);
        const Desc db = make_desc(sb + M_W + s * 14336, 1792, 128, 0);
        wg_fence();
#pragma unroll
        for (int k = 0; k < 4; k++) wgmma_ss_n112_t(acc, da + (kb * 4 + k) * 256, db + k * 224, kb | k);
        wg_commit();
        if (kb > 0) {
            wg_wait<1>();
            if (lane == 0) mbar_arrive(bar_we + 8 * sp);
            if (PART == 1 && lane == 1) mbar_arrive(bar_xe + 8 * (kb - 1));
        }
        sp = s;
        if (++s == M_WS) { s = 0; pw ^= 1; }
    }
    wg_wait<0>();
    if (lane == 0) mbar_arrive(bar_we + 8 * ((PART * 8 + 7) % M_WS));
    if (PART == 1 && lane == 1) mbar_arrive(bar_xe + 8 * 7);
    reg_fence(acc);
    return p;
}
__global__ void __launch_bounds__(640, 1)
k_mix(const __grid_constant__ CUtensorMap tm_wsp, const __nv_bfloat16* __restrict__ b_sp, int use_map) {
    extern __shared__ __align__(1024) uint8_t smem[];
    const uint32_t sb = smem_u32(smem);
    const uint32_t bar_xf = sb + M_AUX, bar_xe = bar_xf + 64, bar_wf = bar_xe + 64, bar_we = bar_wf + 8 * M_WS;
    const int tid = threadIdx.x, warp = __shfl_sync(0xffffffffu, tid >> 5, 0), lane = tid & 31;
    const uint32_t rraw = role_load(use_map);
    if (tid == 512) tm_prefetch(&tm_wsp);
    if (tid == 0) {
        if (sb & 1023) asm volatile("trap;");
        for (int i = 0; i < 8; i++) { mbar_init(bar_xf + 8 * i, 1); mbar_init(bar_xe + 8 * i, 8); }
        for (int i = 0; i < M_WS; i++) { mbar_init(bar_wf + 8 * i, 1); mbar_init(bar_we + 8 * i, 8); }
        fence_mbar_init();
    }
    __syncthreads();
    const int bid = role_get(rraw);
    const int rb = bid >> 3, c = bid & 7;
    if (bid < 0) {
        if (tid == 0) { pdl_launch(); pdl_wait(); spare_hold(2); }
        return;
    }
    TS0(3, 0);
    pdl_launch();
    if (warp >= 16) {
        asm volatile("setmaxnreg.dec.sync.aligned.u32 32;");
        if (warp == 16) {
            if (elect_one()) {
                const uint8_t* hsrc = reinterpret_cast<const uint8_t*>(g_h) + (size_t)rb * 131072;
                pdl_wait();
#pragma unroll
                for (int i = 0; i < 8; i++) {
                    if (i >= M_FA) mbar_wait(bar_xf + 8 * (i - M_FA), 0);
                    mbar_expect_tx(bar_xf + 8 * i, 16384);
                    bulk_load(sb + M_X + i * 16384, hsrc + i * 16384, 16384, bar_xf + 8 * i);
                }
                check_in(2);
#pragma unroll 1
                for (int j = 0; j < 32; j += 8) {
#pragma unroll
                    for (int s = 0; s < 8; s++) {
                        mbar_wait(bar_xe + 8 * s, (j >> 3) & 1);
                        mbar_expect_tx(bar_xf + 8 * s, 16384);
                        tma_load_2d(sb + M_X + s * 16384, &tm_wsp, (j + s) * 64, rb * 128, bar_xf + 8 * s);
                    }
                }
            }
        } else if (warp == 17) {
            if (elect_one()) {
                const uint8_t* wsrc = reinterpret_cast<const uint8_t*>(g_win) + (size_t)c * (8 * 14336);
#pragma unroll
                for (int m = 0; m < 16; m++) {
                    const int s = m % M_WS;
                    if (m >= M_FB && m < M_WS) mbar_wait(bar_wf + 8 * (m - M_FB), 0);
                    if (m >= M_WS) mbar_wait(bar_we + 8 * s, (m / M_WS - 1) & 1);
                    mbar_expect_tx(bar_wf + 8 * s, 14336);
                    bulk_load(sb + M_W + s * 14336, wsrc + (m < 8 ? m : m + 56) * 14336, 14336, bar_wf + 8 * s);
                }
            }
            __syncwarp();
            pdl_wait();
            const uint8_t* src = reinterpret_cast<const uint8_t*>(g_z2) + (size_t)c * (256 * 14 * 128);
            const uint32_t* fl = &g_flag[c * 128 + lane * 4];
            uint32_t j = 0, n = 0, ph = 1, bo = bar_wf + (16 % M_WS) * 8, dst = sb + M_W + (16 % M_WS) * 14336;
            uint32_t bend = bar_wf + M_WS * 8;
            asm volatile("" : "+r"(bend));
#pragma unroll 1
            while (j < 32) {
                const uint4 v = ld_relaxed4(fl);
                const uint32_t wait = ~__ballot_sync(0xffffffffu, (v.x & v.y & v.z & v.w) != 0) >> j;
                const uint32_t je = wait ? j + __ffs(wait) - 1 : 32;
                if (++n > (1u << 22)) asm volatile("trap;");
                if (je == j) continue;
                asm volatile("fence.proxy.async.global;" ::: "memory");
                if (j == 0 && lane == 0) TSP(3, 9);
#pragma unroll 1
                for (; j < je; j++) {
                    mbar_wait(bo + 8 * M_WS, ph);
                    if (elect_one()) {
                        mbar_expect_tx(bo, 14336);
                        bulk_load(dst, src, 14336, bo);
                    }
                    src += 14336; dst += 14336; bo += 8;
                    if (bo == bend) { bo -= M_WS * 8; dst -= M_WS * 14336; ph ^= 1; }
                }
            }
        }
    } else {
      asm volatile("setmaxnreg.inc.sync.aligned.u32 112;");
      if (warp < 8) {
        const int q4 = lane & 3;
        const int r0 = rb * 128 + warp * 16 + (lane >> 2);
        float acc[56], cv[28];
        const MixPre p = mix_gemm1<0>(acc, cv, sb, r0, c, warp >> 2, lane, bid);
        TS0(3, 3);
        float s0 = 0.f, q0 = 0.f, s1 = 0.f, q1 = 0.f;
#pragma unroll
        for (int j = 0; j < 14; j++) {
            const float v0 = gelu_h(p.rstd0 * fmaf(-p.mean0, cv[2 * j], acc[4 * j]));
            const float v1 = gelu_h(p.rstd0 * fmaf(-p.mean0, cv[2 * j + 1], acc[4 * j + 1]));
            const float v2 = gelu_h(p.rstd1 * fmaf(-p.mean1, cv[2 * j], acc[4 * j + 2]));
            const float v3 = gelu_h(p.rstd1 * fmaf(-p.mean1, cv[2 * j + 1], acc[4 * j + 3]));
            acc[4 * j] = v0; acc[4 * j + 1] = v1; acc[4 * j + 2] = v2; acc[4 * j + 3] = v3;
            s0 += v0; q0 = fmaf(v0, v0, q0); s0 += v1; q0 = fmaf(v1, v1, q0);
            s1 += v2; q1 = fmaf(v2, v2, q1); s1 += v3; q1 = fmaf(v3, v3, q1);
        }
        s0 = quad_sum(s0); q0 = quad_sum(q0); s1 = quad_sum(s1); q1 = quad_sum(q1);
        if (q4 < 2) {
            float2* ps = &g_zstat[(r0 + q4 * 8) * 8 + c];
            const float ss = q4 == 0 ? s0 : s1, qq = q4 == 0 ? q0 : q1;
            unsigned long long w;
            asm("mov.b64 %0, {%1,%2};" : "=l"(w) : "f"(ss), "f"(qq));
            asm volatile("st.relaxed.gpu.global.b64 [%0], %1;" ::"l"(ps), "l"(w) : "memory");
        }
        bar_arrive(1, 512);
        TS0(3, 4);
        float4 a, b;
        const float2* pa = &g_zstat[r0 * 8 + q4 * 2];
        const float2* pb = &g_zstat[(r0 + 8) * 8 + q4 * 2];
        uint32_t n = 0;
        while (true) {
            {
                unsigned long long a0, a1, b0, b1;
                asm volatile("ld.relaxed.gpu.global.v2.b64 {%0,%1}, [%2];" : "=l"(a0), "=l"(a1) : "l"(pa) : "memory");
                asm volatile("ld.relaxed.gpu.global.v2.b64 {%0,%1}, [%2];" : "=l"(b0), "=l"(b1) : "l"(pb) : "memory");
                asm("mov.b64 {%0,%1}, %2;" : "=f"(a.x), "=f"(a.y) : "l"(a0));
                asm("mov.b64 {%0,%1}, %2;" : "=f"(a.z), "=f"(a.w) : "l"(a1));
                asm("mov.b64 {%0,%1}, %2;" : "=f"(b.x), "=f"(b.y) : "l"(b0));
                asm("mov.b64 {%0,%1}, %2;" : "=f"(b.z), "=f"(b.w) : "l"(b1));
            }
            const bool bad = (a.y < 0.f) || (a.w < 0.f) || (b.y < 0.f) || (b.w < 0.f);
            if (!__any_sync(0xffffffffu, bad)) break;
            if (++n > (1u << 22)) asm volatile("trap;");
        }
        TS0(3, 8);
        s0 = quad_sum(a.x + a.z); q0 = quad_sum(a.y + a.w); s1 = quad_sum(b.x + b.z); q1 = quad_sum(b.y + b.w);
        const float mu0 = s0 * (1.f / FH), mu1 = s1 * (1.f / FH);
        const float rr0 = rsqrtf(fmaxf(q0 * (1.f / FH) - mu0 * mu0, 0.f) + LN_EPS);
        const float rr1 = rsqrtf(fmaxf(q1 * (1.f / FH) - mu1 * mu1, 0.f) + LN_EPS);
        const float n0 = -mu0 * rr0, n1 = -mu1 * rr1;
        uint32_t* dst = g_z2 + ((c * 256 + rb * 16 + warp * 2) * 14) * 32 + lane;
#pragma unroll
        for (int j = 0; j < 14; j++) {
            dst[j * 32] = pack_bf16(fmaf(acc[4 * j], rr0, n0), fmaf(acc[4 * j + 1], rr0, n0));
            dst[(14 + j) * 32] = pack_bf16(fmaf(acc[4 * j + 2], rr1, n1), fmaf(acc[4 * j + 3], rr1, n1));
        }
        TS0(3, 5);
        __syncwarp();
        if (lane == 0) asm volatile("st.release.gpu.global.u32 [%0], 1;" ::"l"(&g_flag[c * 128 + rb * 8 + warp]) : "memory");
        TS0(3, 7);
      } else {
        const int wm = (warp >> 2) & 1, w8 = warp & 7;
        const int r0 = rb * 128 + w8 * 16 + (lane >> 2);
        float acc[56];
        uint32_t z1[28];
        {
            float cv[28];
            const MixPre p = mix_gemm1<1>(acc, cv, sb, r0, c, wm, lane, bid);
            if (warp == 8) TS(3, 6);
#pragma unroll
            for (int j = 0; j < 14; j++) {
                z1[2 * j] = pack_bf16(gelu_h(p.rstd0 * fmaf(-p.mean0, cv[2 * j], acc[4 * j])), gelu_h(p.rstd0 * fmaf(-p.mean0, cv[2 * j + 1], acc[4 * j + 1])));
                z1[2 * j + 1] = pack_bf16(gelu_h(p.rstd1 * fmaf(-p.mean1, cv[2 * j], acc[4 * j + 2])), gelu_h(p.rstd1 * fmaf(-p.mean1, cv[2 * j + 1], acc[4 * j + 3])));
            }
            reg_fence(z1);
#pragma unroll
            for (int j = 0; j < 56; j++) asm volatile("" : "=f"(acc[j]));
            if (warp == 8) TS(3, 13);
        }
        const unsigned short braw0 = __ldg(reinterpret_cast<const unsigned short*>(b_sp) + r0);
        const unsigned short braw1 = __ldg(reinterpret_cast<const unsigned short*>(b_sp) + r0 + 8);
        uint32_t sw = 16 % M_WS, pw = (16 / M_WS) & 1, rel = 0;
#pragma unroll 1
        for (int kb = 0; kb < 32; kb++) {
            const uint32_t sa = kb & 7;
            mbar_wait(bar_xf + 8 * sa, ((kb >> 3) + 1) & 1);
            mbar_wait(bar_wf + 8 * sw, pw);
            if (kb == 0 && warp == 8) TS(3, 10);
            if ((kb & 3) == 0 && kb && warp == 8) TS(3, 14 + kb / 4);
            const Desc da = make_desc(sb + M_X + sa * 16384 + wm * 8192, 16, 1024, 1);
            const Desc db = make_desc(sb + M_W + sw * 14336, 1792, 128, 0);
            wg_fence();
#pragma unroll
            for (int k = 0; k < 4; k++) wgmma_ss_n112_t(acc, da + k * 2, db + k * 224, kb | k);
            wg_commit();
            wg_wait<1>();
            if (kb > 0 && lane < 2) mbar_arrive(rel);
            rel = lane == 0 ? bar_we + 8 * sw : bar_xe + 8 * sa;
            if (++sw == M_WS) { sw = 0; pw ^= 1; }
        }
        wg_wait<0>();
        reg_fence(acc);
        if (warp == 8) TS(3, 11);
        const float bias0 = __uint_as_float((uint32_t)braw0 << 16), bias1 = __uint_as_float((uint32_t)braw1 << 16);
        uint32_t* dst = g_u + ((rb * 112 + c * 14) * 16 + w8 * 2) * 32 + lane;
#pragma unroll
        for (int j = 0; j < 14; j++) {
            const uint32_t za = z1[2 * j], zb = z1[2 * j + 1];
            dst[j * 512] = pack_bf16(bf_lo(za) * (acc[4 * j] + bias0), bf_hi(za) * (acc[4 * j + 1] + bias0));
            dst[j * 512 + 32] = pack_bf16(bf_lo(zb) * (acc[4 * j + 2] + bias1), bf_hi(zb) * (acc[4 * j + 3] + bias1));
        }
        if (warp == 8) TS(3, 12);
      }
    }
}

constexpr int P6_AS = 4;
constexpr int P6_A = 0, P6_B = P6_AS * 28672, P6_AUX = P6_B + 8 * 14336;
constexpr int P6_SMEM = P6_AUX + 256;
#define P6_FA 3
#define P6_FB 2
__global__ void __launch_bounds__(320, 1)
k_wout(const __grid_constant__ CUtensorMap tm_wout, const __grid_constant__ CUtensorMap tm_out, int use_map) {
    extern __shared__ __align__(1024) uint8_t smem[];
    const uint32_t sb = smem_u32(smem);
    const uint32_t bar_af = sb + P6_AUX, bar_ae = bar_af + 8 * P6_AS, bar_b = bar_ae + 8 * P6_AS;
    const int tid = threadIdx.x, warp = __shfl_sync(0xffffffffu, tid >> 5, 0), lane = tid & 31;
    const uint32_t rraw = role_load(use_map);
    if (tid == 288) { tm_prefetch(&tm_wout); tm_prefetch(&tm_out); }
    if (tid == 0) {
        if (sb & 1023) asm volatile("trap;");
        for (int i = 0; i < P6_AS; i++) { mbar_init(bar_af + 8 * i, 1); mbar_init(bar_ae + 8 * i, 8); }
        for (int i = 0; i < 8; i++) mbar_init(bar_b + 8 * i, 1);
        fence_mbar_init();
    }
    __syncthreads();
    const int bid = role_get(rraw), rb = bid >> 3, c = bid & 7;
    if (bid < 0) {
        if (tid == 0) { pdl_wait(); spare_hold(3); }
        return;
    }
    TS0(5, 0);
    if (warp == 8) {
        if (elect_one()) {
            pdl_wait();
            const uint8_t* src = reinterpret_cast<const uint8_t*>(g_u) + (size_t)rb * (112 * 16 * 128);
#pragma unroll
            for (int i = 0; i < 8; i++) {
                int s = i % P6_AS;
                if (i == P6_FA) { check_in(3); g_role[sm_id()] = 0; }
                if (i >= P6_FA) mbar_wait(bar_af + 8 * ((i - P6_FA) % P6_AS), ((i - P6_FA) / P6_AS) & 1);
                if (i >= P6_AS) mbar_wait(bar_ae + 8 * s, 0);
                mbar_expect_tx(bar_af + 8 * s, 28672);
                bulk_load(sb + P6_A + s * 28672, src + (size_t)i * 28672, 28672, bar_af + 8 * s);
            }
        }
    } else if (warp == 9) {
        if (elect_one()) {
            for (int i = 0; i < 8; i++) {
                if (i >= P6_FB) mbar_wait(bar_b + 8 * (i - P6_FB), 0);
                mbar_expect_tx(bar_b + 8 * i, 14336);
                tma_load_2d(sb + P6_B + i * 14336, &tm_wout, c * 64, i * 112, bar_b + 8 * i);
            }
        }
    } else {
        const int wg = warp >> 2;
        pdl_wait();
        TS0(5, 1);
        uint32_t hr[16];
        {
            const uint32_t* src = g_h + ((rb * 64 + c * 8) * 16 + warp * 2) * 32 + lane;
#pragma unroll
            for (int j = 0; j < 8; j++) { hr[2 * j] = src[j * 512]; hr[2 * j + 1] = src[j * 512 + 32]; }
        }
        float acc[32];
        for (int kb = 0; kb < 8; kb++) {
            const int s = kb % P6_AS;
            mbar_wait(bar_b + 8 * kb, 0);
            mbar_wait(bar_af + 8 * s, (kb / P6_AS) & 1);
            if (kb == 0) TS0(5, 2);
            const Desc da = make_desc(sb + P6_A + s * 28672 + wg * 1024, 2048, 128, 0);
            const Desc db = make_desc(sb + P6_B + kb * 14336, 8192, 1024, 1);
            wg_fence();
#pragma unroll
            for (int k = 0; k < 7; k++) wgmma_ss_n64_t(acc, da + k * 256, db + k * 128, kb | k);
            wg_commit();
            if (kb > 0) {
                wg_wait<1>();
                if (lane == 0) mbar_arrive(bar_ae + 8 * ((kb - 1) % P6_AS));
            }
        }
        wg_wait<0>();
        reg_fence(acc);
        TS0(5, 3);
        bar_sync(1, 256);
        const uint32_t so = sb + P6_B + warp * 2048;
#pragma unroll
        for (int jp = 0; jp < 4; jp++) {
            uint32_t r[4];
#pragma unroll
            for (int e = 0; e < 2; e++) {
                const int j = jp * 2 + e;
                r[2 * e] = pack_bf16(acc[4 * j] + bf_lo(hr[2 * j]), acc[4 * j + 1] + bf_hi(hr[2 * j]));
                r[2 * e + 1] = pack_bf16(acc[4 * j + 2] + bf_lo(hr[2 * j + 1]), acc[4 * j + 3] + bf_hi(hr[2 * j + 1]));
            }
            const int mt = lane >> 3, rr = (lane & 7) + (mt & 1) * 8, chn = jp * 2 + (mt >> 1);
            const uint32_t addr = so + rr * 128 + ((chn ^ (rr & 7)) << 4);
            asm volatile("stmatrix.sync.aligned.m8n8.x4.shared.b16 [%0], {%1,%2,%3,%4};" ::"r"(addr), "r"(r[0]), "r"(r[1]), "r"(r[2]), "r"(r[3]) : "memory");
        }
        fence_proxy_async();
        bar_sync(1, 256);
        if (warp == 0 && elect_one()) {
            tma_store_2d(&tm_out, sb + P6_B, c * 64, rb * 128);
            asm volatile("cp.async.bulk.commit_group;" ::: "memory");
            asm volatile("cp.async.bulk.wait_group.read 0;" ::: "memory");
            TSP(5, 4);
        }
    }
}

typedef CUresult (*EncodeFn)(CUtensorMap*, CUtensorMapDataType, cuuint32_t, void*, const cuuint64_t*, const cuuint64_t*,
                             const cuuint32_t*, const cuuint32_t*, CUtensorMapInterleave, CUtensorMapSwizzle,
                             CUtensorMapL2promotion, CUtensorMapFloatOOBfill);

void make_map(EncodeFn fn, CUtensorMap* tm, const void* ptr, uint64_t inner, uint64_t outer, uint32_t bi, uint32_t bo) {
    cuuint64_t dims[2] = {inner, outer};
    cuuint64_t strides[1] = {inner * 2};
    cuuint32_t box[2] = {bi, bo};
    cuuint32_t es[2] = {1, 1};
    fn(tm, CU_TENSOR_MAP_DATA_TYPE_BFLOAT16, 2, const_cast<void*>(ptr), dims, strides, box, es, CU_TENSOR_MAP_INTERLEAVE_NONE,
       CU_TENSOR_MAP_SWIZZLE_128B, CU_TENSOR_MAP_L2_PROMOTION_L2_256B, CU_TENSOR_MAP_FLOAT_OOB_FILL_NONE);
}

template <typename... KArgs, typename... Args>
void launch(void (*kern)(KArgs...), int grid, int block, int smem, bool pdl, int cluster, Args... args) {
    cudaLaunchConfig_t cfg = {};
    cfg.gridDim = dim3(grid); cfg.blockDim = dim3(block); cfg.dynamicSmemBytes = smem; cfg.stream = cudaStreamPerThread;
    cudaLaunchAttribute at[2];
    int n = 0;
    if (pdl) {
        at[n].id = cudaLaunchAttributeProgrammaticStreamSerialization;
        at[n].val.programmaticStreamSerializationAllowed = 1;
        n++;
    }
    if (cluster > 1) {
        at[n].id = cudaLaunchAttributeClusterDimension;
        at[n].val.clusterDim.x = cluster; at[n].val.clusterDim.y = 1; at[n].val.clusterDim.z = 1;
        n++;
    }
    cfg.attrs = at; cfg.numAttrs = n;
    cudaLaunchKernelEx(&cfg, kern, KArgs(args)...);
}

}

extern "C" void kernel_launch(void* const* d_in, const int* in_sizes, int n_in, void* d_out, int out_size) {
    (void)in_sizes; (void)n_in; (void)out_size;
    const __nv_bfloat16* x = (const __nv_bfloat16*)d_in[0];
    const __nv_bfloat16* wqkv = (const __nv_bfloat16*)d_in[1];
    const __nv_bfloat16* wo = (const __nv_bfloat16*)d_in[2];
    const __nv_bfloat16* w_in = (const __nv_bfloat16*)d_in[4];
    const __nv_bfloat16* w_sp = (const __nv_bfloat16*)d_in[5];
    const __nv_bfloat16* b_sp = (const __nv_bfloat16*)d_in[6];
    const __nv_bfloat16* w_out = (const __nv_bfloat16*)d_in[7];

    static EncodeFn enc = nullptr;
    static int nsm = 0;
    if (!enc) {
        void* fp = nullptr;
        cudaDriverEntryPointQueryResult qr;
        cudaGetDriverEntryPoint("cuTensorMapEncodeTiled", &fp, cudaEnableDefault, &qr);
        enc = (EncodeFn)fp;
        int dev = 0;
        cudaGetDevice(&dev);
        cudaDeviceGetAttribute(&nsm, cudaDevAttrMultiProcessorCount, dev);
        cudaFuncSetAttribute(k_qkv, cudaFuncAttributeMaxDynamicSharedMemorySize, P1_SMEM);
        cudaFuncSetAttribute(k_attn, cudaFuncAttributeMaxDynamicSharedMemorySize, P2_SMEM);
        cudaFuncSetAttribute(k_oproj, cudaFuncAttributeMaxDynamicSharedMemorySize, P3_SMEM);
        cudaFuncSetAttribute(k_mix, cudaFuncAttributeMaxDynamicSharedMemorySize, M_SMEM);
        cudaFuncSetAttribute(k_wout, cudaFuncAttributeMaxDynamicSharedMemorySize, P6_SMEM);
    }
    CUtensorMap tm_x, tm_wqkv, tm_wo, tm_wsp, tm_wout, tm_out;
    make_map(enc, &tm_x, x, DM, SEQ, 64, 128);
    make_map(enc, &tm_wqkv, wqkv, 3 * DM, DM, 64, 64);
    make_map(enc, &tm_wo, wo, DM, DM, 64, 64);
    make_map(enc, &tm_wsp, w_sp, SEQ, SEQ, 64, 128);
    make_map(enc, &tm_wout, w_out, DM, FH, 64, 112);
    make_map(enc, &tm_out, d_out, DM, SEQ, 64, 128);

    launch(k_qkv, 128, 416, P1_SMEM, false, 1, tm_x, tm_wqkv, x, wqkv);
    const int um = nsm >= 132 && nsm <= 1024;
    const int g1 = um ? nsm : 132, g2 = um ? nsm : 128;
    launch(k_attn, g1, 544, P2_SMEM, true, 1, w_in, wo, w_sp, w_out, um);
    launch(k_oproj, g2, 320, P3_SMEM, true, 1, tm_wo, x, um);
    launch(k_mix, g2, 640, M_SMEM, true, 1, tm_wsp, b_sp, um);
    launch(k_wout, g2, 320, P6_SMEM, true, 1, tm_wout, tm_out, um);
}
```
